```python
import torch

def _softmax(x, axis=-1):
    return torch.softmax(x, dim=axis)
def _gelu(x):
    return torch.nn.functional.gelu(x, approximate="tanh")
def _silu(x):
    return torch.nn.functional.silu(x)
def _sigmoid(x):
    return torch.sigmoid(x)
def _layernorm(x, axis=-1, eps=1e-5):
    m = x.mean(dim=axis, keepdim=True)
    v = x.var(dim=axis, keepdim=True, unbiased=False)
    return (x - m) / torch.sqrt(v + eps)
def _scatter_add(tgt, idx, src, axis=0):
    return tgt.clone().index_add_(axis, idx, src)
def _segment_sum(src, seg, n):
    out = torch.zeros((n,) + src.shape[1:], dtype=src.dtype)
    return out.index_add_(0, seg, src)
def _pad(x, pw):
    flat = tuple(v for pair in reversed(pw) for v in pair)
    return torch.nn.functional.pad(x, flat)

kernel_name = 'interleave_layers__sliding_local_dilated__ssm_conv_h3__prompt'

def setup_inputs():

    _w = (lambda a: (lambda t: t.to(torch.bfloat16) if t.is_floating_point() else t)(torch.as_tensor(a)))
    def _A_setup():
        B, S, D = 1, 2048, 512
        return {
            "x": _w((lambda *s: torch.randn(*s, dtype=torch.bfloat16) * 0.05)(B, S, D)),
            "wqkv": _w((lambda *s: torch.randn(*s, dtype=torch.bfloat16) * 0.05)(D, 3 * D)),
            "wo": _w((lambda *s: torch.randn(*s, dtype=torch.bfloat16) * 0.05)(D, D)),
        }
    _A_in = _A_setup()

    def _B_setup():
        B, S, D = 1, 2048, 512
        ks = 4
        return {
            "q": _w((lambda *s: torch.randn(*s, dtype=torch.bfloat16) * 0.05)(B, S, D)),
            "k": _w((lambda *s: torch.randn(*s, dtype=torch.bfloat16) * 0.4)(B, S, D)),
            "v": _w((lambda *s: torch.randn(*s, dtype=torch.bfloat16) * 0.4)(B, S, D)),
            "shift_k": _w((lambda *s: torch.randn(*s, dtype=torch.bfloat16) * 0.4)(D, ks) * 0.5),
            "ssm_k": _w((lambda *s: torch.randn(*s, dtype=torch.bfloat16) * 0.8)(D, S) * (1.0 / S ** 0.5)),
            "ssm_D": _w((lambda *s: torch.randn(*s, dtype=torch.bfloat16) * 0.4)(D)),
        }
    _B_in = _B_setup()

    return {
        "A_x": _A_in["x"],
        "A_wqkv": _A_in["wqkv"],
        "A_wo": _A_in["wo"],
        "B_q": _B_in["q"],
        "B_k": _B_in["k"],
        "B_v": _B_in["v"],
        "B_shift_k": _B_in["shift_k"],
        "B_ssm_k": _B_in["ssm_k"],
        "B_ssm_D": _B_in["ssm_D"],
    }

def reference(A_x, A_wqkv, A_wo, B_q, B_k, B_v, B_shift_k, B_ssm_k, B_ssm_D):
    def _A_ref(x, wqkv, wo):
        B, S, D = x.shape
        H = 32; Dh = D // H
        W, dil = 8, 2
        qkv = (lambda x, *d: x.permute(*d))((x @ wqkv).reshape(B, S, 3, H, Dh), 2, 0, 3, 1, 4)
        q, k, v = qkv[0], qkv[1], qkv[2]
        scale = Dh ** -0.5
        pos = torch.arange(S)
        off = torch.arange(W) * dil
        idx = pos[:, None] - off[None, :]
        mask = idx >= 0
        idx_c = torch.where(mask, idx, 0).reshape(-1)
        kg = k[:, :, idx_c, :].reshape(B, H, S, W, Dh)
        vg = v[:, :, idx_c, :].reshape(B, H, S, W, Dh)
        logits = torch.einsum("bhsd,bhswd->bhsw", q, kg) * scale
        logits = torch.where(mask[None, None, :, :], logits, -1e9)
        attn = _softmax(logits, axis=-1)
        o = torch.einsum("bhsw,bhswd->bhsd", attn, vg)
        return (lambda x, *d: x.permute(*d))(o, 0, 2, 1, 3).reshape(B, S, D) @ wo

    def _B_ref(q, k, v, shift_k, ssm_k, ssm_D):
        B, S, D = q.shape
        ks = shift_k.shape[-1]
        k_pad = _pad(k, ((0, 0), (ks - 1, 0), (0, 0)))
        k_shift = torch.zeros_like(k)
        for t in range(ks):
            k_shift = k_shift + k_pad[:, t:t + S, :] * shift_k[:, ks - 1 - t][None, None, :]
        kv = k_shift * v
        L = 2 * S
        kv_pad = _pad(kv, ((0, 0), (0, S), (0, 0)))
        kf_pad = _pad(ssm_k, ((0, 0), (0, S)))
        kv_f = (lambda x, axes=(-2,-1): torch.fft.rfft2(x.float(), dim=axes))(kv_pad[:, None, :, :], axes=(1, 2))
        kf_f = (lambda x, axes=(-2,-1): torch.fft.rfft2(x.float(), dim=axes))(kf_pad[:, None, :], axes=(1, 2))
        kf_f = (lambda x, *d: x.permute(*d))(kf_f, 1, 2, 0)
        y_f = kv_f * kf_f[None, :, :, :]
        y = (lambda x, s, axes=(-2,-1): torch.fft.irfft2(x, s=s, dim=axes).to(torch.bfloat16))(y_f, (1, L), axes=(1, 2))[:, 0, :S, :]
        y = y + kv * ssm_D[None, None, :]
        return q * y

    x = A_x
    x = x + _A_ref(_layernorm(x, axis=-1), A_wqkv, A_wo)
    x = x + _B_ref(_layernorm(x, axis=-1), B_k, B_v, B_shift_k, B_ssm_k, B_ssm_D)
    x = x + _A_ref(_layernorm(x, axis=-1), A_wqkv, A_wo)
    x = x + _B_ref(_layernorm(x, axis=-1), B_k, B_v, B_shift_k, B_ssm_k, B_ssm_D)
    return x
```

```cpp
#include <cuda_runtime.h>
#include <cuda_bf16.h>
#include <cuda.h>
#include <stdint.h>

#define DEVI __device__ __forceinline__

#define PROFILE 0

namespace {

constexpr int NT = 15;
constexpr int XSLOT = 19456;
constexpr int SUBT = 4864;
constexpr int RSLOT = 8192;
constexpr int STAG = 190;
constexpr int NRING = 6;
constexpr int OFF_X = 0;
constexpr int OFF_RING = 8 * XSLOT;
constexpr int OFF_STQ = OFF_RING + NRING * RSLOT;
constexpr int OFF_BAR = OFF_STQ + 8 * 1216;
constexpr int OFF_STB = OFF_BAR + 896;
constexpr int OFF_MRB = OFF_STB + 8 * 1152;
constexpr int OFF_URAW = OFF_STB;
constexpr int OFF_PROF = OFF_URAW + 16384;
constexpr int SMEM_MAIN = OFF_PROF + (PROFILE ? 640 : 0);
static_assert(SMEM_MAIN <= 232448, "smem");

constexpr int UAP = 2320;
constexpr int UCH = 4 * UAP;
constexpr int HCP = 560;
constexpr int KIN = 17 * 8 * 64, VIN = 16 * 8 * 64;
constexpr int KVIN = KIN + VIN + 256;

enum { B_FULL = 0, B_XOWN = 35, B_XFULL = 68, B_KIN = 76, B_VIN, B_URAW, B_STQ, B_STB, B_MRQ,
       B_KFREE = 84, B_OSTORED, B_XFREE, B_KQDONE, B_CVD,
       B_EMPTY = 91, B_STAGED = 97, B_ATTLD, B_TD,
       B_HFREE = B_TD + 4, B_YST, B_TAB = B_YST + 4,
       B_COUNT = B_TAB + 4 };
constexpr unsigned OSEQ1 = 0x23715460u;
constexpr unsigned HSLOT = 0x3754u;

}

__device__ __align__(1024) __nv_bfloat16 g_Y[512 * 2048];
__device__ __align__(1024) uint8_t g_exO[NT * 8 * XSLOT];
__device__ __align__(1024) uint8_t g_exX[NT * 8 * XSLOT];
__device__ __align__(1024) __nv_bfloat16 g_U[512 * 2048];
__device__ unsigned g_ycnt[8];
__device__ unsigned g_ucnt;
__device__ unsigned g_done;
#define STAMP(i) do {} while (0)

DEVI uint32_t s2u(const void* p) { return (uint32_t)__cvta_generic_to_shared(p); }
DEVI void mbar_init(uint32_t b, int c) { asm volatile("mbarrier.init.shared::cta.b64 [%0], %1;" ::"r"(b), "r"(c) : "memory"); }
DEVI void mbar_expect(uint32_t b, uint32_t bytes) {
  asm volatile("mbarrier.arrive.expect_tx.shared::cta.b64 _, [%0], %1;" ::"r"(b), "r"(bytes) : "memory");
}
DEVI void mbar_arrive(uint32_t b) { asm volatile("mbarrier.arrive.shared::cta.b64 _, [%0];" ::"r"(b) : "memory"); }
DEVI void mbar_arrive_n(uint32_t b, int n) { asm volatile("mbarrier.arrive.shared::cta.b64 _, [%0], %1;" ::"r"(b), "r"(n) : "memory"); }
DEVI void mbar_arrive_remote(uint32_t b) {
  asm volatile("mbarrier.arrive.relaxed.cluster.shared::cluster.b64 _, [%0];" ::"r"(b) : "memory");
}
DEVI uint32_t clk32() { uint32_t t; asm volatile("mov.u32 %0,%%clock;" : "=r"(t)); return t; }
DEVI bool expired(uint32_t t0) { return clk32() - t0 > (1u << 28); }
DEVI void mbar_wait(uint32_t b, uint32_t ph, uint32_t t0) {
  uint32_t ok;
  do {
    asm volatile("{.reg .pred p; mbarrier.try_wait.parity.shared::cta.b64 p,[%1],%2; selp.u32 %0,1,0,p;}"
                 : "=r"(ok) : "r"(b), "r"(ph) : "memory");
  } while (!ok && !expired(t0));
}
DEVI void mbar_wait_cl(uint32_t b, uint32_t ph, uint32_t t0) {
  uint32_t ok;
  do {
    asm volatile("{.reg .pred p; mbarrier.try_wait.parity.acquire.cluster.shared::cta.b64 p,[%1],%2; selp.u32 %0,1,0,p;}"
                 : "=r"(ok) : "r"(b), "r"(ph) : "memory");
  } while (!ok && !expired(t0));
}
DEVI bool mbar_test(uint32_t b, uint32_t ph) {
  uint32_t ok;
  asm volatile("{.reg .pred p; mbarrier.test_wait.parity.shared::cta.b64 p,[%1],%2; selp.u32 %0,1,0,p;}"
               : "=r"(ok) : "r"(b), "r"(ph) : "memory");
  return ok;
}
DEVI uint32_t mapa(uint32_t a, uint32_t r) {
  uint32_t o;
  asm("mapa.shared::cluster.u32 %0,%1,%2;" : "=r"(o) : "r"(a), "r"(r));
  return o;
}
DEVI void fence_async() { asm volatile("fence.proxy.async;" ::: "memory"); }
DEVI void fence_async_smem() { asm volatile("fence.proxy.async.shared::cta;" ::: "memory"); }
DEVI void bar_sync(int id, int n) { __syncwarp(); asm volatile("bar.sync %0,%1;" ::"r"(id), "r"(n) : "memory"); }
DEVI void bar_arrive(int id, int n) { __syncwarp(); asm volatile("bar.arrive %0,%1;" ::"r"(id), "r"(n) : "memory"); }
DEVI void tma2d(uint32_t dst, const CUtensorMap* tm, int x, int y, uint32_t bar) {
  asm volatile("cp.async.bulk.tensor.2d.shared::cluster.global.mbarrier::complete_tx::bytes [%0],[%1,{%3,%4}],[%2];"
               ::"r"(dst), "l"(tm), "r"(bar), "r"(x), "r"(y) : "memory");
}
DEVI void tma3d(uint32_t dst, const CUtensorMap* tm, int x, int y, int z, uint32_t bar) {
  asm volatile("cp.async.bulk.tensor.3d.shared::cluster.global.mbarrier::complete_tx::bytes [%0],[%1,{%3,%4,%5}],[%2];"
               ::"r"(dst), "l"(tm), "r"(bar), "r"(x), "r"(y), "r"(z) : "memory");
}
DEVI void tma3d_store(const CUtensorMap* tm, int x, int y, int z, uint32_t src) {
  asm volatile("cp.async.bulk.tensor.3d.global.shared::cta.bulk_group [%0,{%2,%3,%4}],[%1];" ::"l"(tm), "r"(src), "r"(x), "r"(y), "r"(z) : "memory");
}
DEVI void flag_wait(const unsigned* p, unsigned target, uint32_t t0) {
  unsigned v;
  while (true) {
    asm volatile("ld.relaxed.gpu.global.u32 %0,[%1];" : "=r"(v) : "l"(p) : "memory");
    if (v >= target || expired(t0)) break;
    __nanosleep(40);
  }
}
DEVI void tma2d_mc(uint32_t dst, const CUtensorMap* tm, int x, int y, uint32_t bar, uint16_t mask) {
  asm volatile("cp.async.bulk.tensor.2d.shared::cluster.global.mbarrier::complete_tx::bytes.multicast::cluster [%0],[%1,{%3,%4}],[%2],%5;"
               ::"r"(dst), "l"(tm), "r"(bar), "r"(x), "r"(y), "h"(mask) : "memory");
}
DEVI void tma2d_store(const CUtensorMap* tm, int x, int y, uint32_t src) {
  asm volatile("cp.async.bulk.tensor.2d.global.shared::cta.bulk_group [%0,{%2,%3}],[%1];" ::"l"(tm), "r"(src), "r"(x), "r"(y) : "memory");
}
DEVI void bulk_load(uint32_t dst, const void* src, uint32_t bytes, uint32_t bar) {
  asm volatile("cp.async.bulk.shared::cluster.global.mbarrier::complete_tx::bytes [%0],[%1],%2,[%3];"
               ::"r"(dst), "l"(src), "r"(bytes), "r"(bar) : "memory");
}
DEVI void bulk_load_mc(uint32_t dst, const void* src, uint32_t bytes, uint32_t bar, uint16_t mask) {
  asm volatile("cp.async.bulk.shared::cluster.global.mbarrier::complete_tx::bytes.multicast::cluster [%0],[%1],%2,[%3],%4;"
               ::"r"(dst), "l"(src), "r"(bytes), "r"(bar), "h"(mask) : "memory");
}
DEVI void bulk_s2s(uint32_t dst, uint32_t src, uint32_t bytes, uint32_t bar) {
  asm volatile("cp.async.bulk.shared::cluster.shared::cta.mbarrier::complete_tx::bytes [%0],[%1],%2,[%3];"
               ::"r"(dst), "r"(src), "r"(bytes), "r"(bar) : "memory");
}
DEVI void bulk_store(void* dst, uint32_t src, uint32_t bytes) {
  asm volatile("cp.async.bulk.global.shared::cta.bulk_group [%0],[%1],%2;" ::"l"(dst), "r"(src), "r"(bytes) : "memory");
}
DEVI void l2_prefetch(const void* src, uint32_t bytes) {
  asm volatile("cp.async.bulk.prefetch.L2.global [%0],%1;" ::"l"(src), "r"(bytes) : "memory");
}
DEVI void bulk_commit() { asm volatile("cp.async.bulk.commit_group;" ::: "memory"); }
DEVI void bulk_wait0() { asm volatile("cp.async.bulk.wait_group 0;" ::: "memory"); }
DEVI void bulk_wait0_read() { asm volatile("cp.async.bulk.wait_group.read 0;" ::: "memory"); }
DEVI void st_async2(uint32_t dst, float a, float b, uint32_t bar) {
  asm volatile("st.async.weak.shared::cluster.mbarrier::complete_tx::bytes.v2.f32 [%0],{%1,%2},[%3];"
               ::"r"(dst), "f"(a), "f"(b), "r"(bar) : "memory");
}
DEVI void st_async4(uint32_t dst, uint32_t a, uint32_t b, uint32_t c, uint32_t d, uint32_t bar) {
  asm volatile("st.async.weak.shared::cluster.mbarrier::complete_tx::bytes.v4.b32 [%0],{%1,%2,%3,%4},[%5];"
               ::"r"(dst), "r"(a), "r"(b), "r"(c), "r"(d), "r"(bar) : "memory");
}
DEVI void wg_fence() { asm volatile("wgmma.fence.sync.aligned;" ::: "memory"); }
DEVI void wg_commit() { asm volatile("wgmma.commit_group.sync.aligned;" ::: "memory"); }
template <int N> DEVI void wg_wait() { asm volatile("wgmma.wait_group.sync.aligned %0;" ::"n"(N) : "memory"); }
DEVI uint64_t mkdesc(uint32_t addr, uint32_t lbo, uint32_t sbo, uint32_t swz) {
  return (uint64_t)((addr & 0x3FFFF) >> 4) | ((uint64_t)(lbo >> 4) << 16) | ((uint64_t)(sbo >> 4) << 32) | ((uint64_t)swz << 62);
}
DEVI uint64_t desc64(uint32_t lo, uint32_t hi) {
  uint64_t d;
  asm("mov.b64 %0,{%1,%2};" : "=l"(d) : "r"(lo), "r"(hi));
  return d;
}
DEVI uint32_t pin(uint32_t v) { asm volatile("" : "+r"(v)); return v; }
DEVI bool elect() {
  uint32_t p;
  asm volatile("{.reg .pred p; elect.sync _|p,0xffffffff; selp.u32 %0,1,0,p;}" : "=r"(p));
  return p;
}
DEVI int uni(int v) { return __shfl_sync(~0u, v, 0); }
DEVI void mma16816(float* c, uint32_t a0, uint32_t a1, uint32_t a2, uint32_t a3, uint32_t b0, uint32_t b1) {
  asm volatile("mma.sync.aligned.m16n8k16.row.col.f32.bf16.bf16.f32 {%0,%1,%2,%3},{%4,%5,%6,%7},{%8,%9},{%0,%1,%2,%3};"
               : "+f"(c[0]), "+f"(c[1]), "+f"(c[2]), "+f"(c[3]) : "r"(a0), "r"(a1), "r"(a2), "r"(a3), "r"(b0), "r"(b1));
}
DEVI void mma16816_z(float* c, uint32_t a0, uint32_t a1, uint32_t a2, uint32_t a3, uint32_t b0, uint32_t b1) {
  asm volatile("mma.sync.aligned.m16n8k16.row.col.f32.bf16.bf16.f32 {%0,%1,%2,%3},{%4,%5,%6,%7},{%8,%9},{%10,%10,%10,%10};"
               : "=f"(c[0]), "=f"(c[1]), "=f"(c[2]), "=f"(c[3]) : "r"(a0), "r"(a1), "r"(a2), "r"(a3), "r"(b0), "r"(b1), "f"(0.f));
}
DEVI uint32_t pack2(float lo, float hi) {
  uint32_t r;
  asm("cvt.rn.bf16x2.f32 %0,%1,%2;" : "=r"(r) : "f"(hi), "f"(lo));
  return r;
}
DEVI float bflo(uint32_t v) { return __uint_as_float(v << 16); }
DEVI float bfhi(uint32_t v) { return __uint_as_float(v & 0xffff0000u); }
DEVI uint32_t movm(uint32_t a) {
  uint32_t d;
  asm volatile("movmatrix.sync.aligned.m8n8.trans.b16 %0,%1;" : "=r"(d) : "r"(a));
  return d;
}
DEVI void ldsm4(uint32_t* r, uint32_t a) {
  asm volatile("ldmatrix.sync.aligned.m8n8.x4.shared.b16 {%0,%1,%2,%3},[%4];" : "=r"(r[0]), "=r"(r[1]), "=r"(r[2]), "=r"(r[3]) : "r"(a) : "memory");
}
DEVI void ldsm2(uint32_t* r, uint32_t a) {
  asm volatile("ldmatrix.sync.aligned.m8n8.x2.shared.b16 {%0,%1},[%2];" : "=r"(r[0]), "=r"(r[1]) : "r"(a) : "memory");
}
DEVI void ldsm4t(uint32_t* r, uint32_t a) {
  asm volatile("ldmatrix.sync.aligned.m8n8.x4.trans.shared.b16 {%0,%1,%2,%3},[%4];" : "=r"(r[0]), "=r"(r[1]), "=r"(r[2]), "=r"(r[3]) : "r"(a) : "memory");
}
DEVI void ldsm2t(uint32_t* r, uint32_t a) {
  asm volatile("ldmatrix.sync.aligned.m8n8.x2.trans.shared.b16 {%0,%1},[%2];" : "=r"(r[0]), "=r"(r[1]) : "r"(a) : "memory");
}
DEVI void stsm4t(uint32_t a, uint32_t r0, uint32_t r1, uint32_t r2, uint32_t r3) {
  asm volatile("stmatrix.sync.aligned.m8n8.x4.trans.shared.b16 [%0],{%1,%2,%3,%4};" ::"r"(a), "r"(r0), "r"(r1), "r"(r2), "r"(r3) : "memory");
}
DEVI void stsm2t(uint32_t a, uint32_t r0, uint32_t r1) {
  asm volatile("stmatrix.sync.aligned.m8n8.x2.trans.shared.b16 [%0],{%1,%2};" ::"r"(a), "r"(r0), "r"(r1) : "memory");
}
DEVI uint32_t lds32(uint32_t a) { uint32_t v; asm volatile("ld.shared.u32 %0,[%1];" : "=r"(v) : "r"(a) : "memory"); return v; }
DEVI float2 lds64f(uint32_t a) { float2 v; asm volatile("ld.shared.v2.f32 {%0,%1},[%2];" : "=f"(v.x), "=f"(v.y) : "r"(a) : "memory"); return v; }
DEVI float4 lds128f(uint32_t a) {
  float4 v;
  asm volatile("ld.shared.v4.f32 {%0,%1,%2,%3},[%4];" : "=f"(v.x), "=f"(v.y), "=f"(v.z), "=f"(v.w) : "r"(a) : "memory");
  return v;
}
DEVI uint4 lds128(uint32_t a) {
  uint4 v;
  asm volatile("ld.shared.v4.u32 {%0,%1,%2,%3},[%4];" : "=r"(v.x), "=r"(v.y), "=r"(v.z), "=r"(v.w) : "r"(a) : "memory");
  return v;
}
DEVI void sts16(uint32_t a, uint32_t v) { asm volatile("st.shared.u16 [%0],%1;" ::"r"(a), "h"((uint16_t)v) : "memory"); }
DEVI void sts32(uint32_t a, uint32_t v) { asm volatile("st.shared.u32 [%0],%1;" ::"r"(a), "r"(v) : "memory"); }
DEVI void sts64f(uint32_t a, float x, float y) { asm volatile("st.shared.v2.f32 [%0],{%1,%2};" ::"r"(a), "f"(x), "f"(y) : "memory"); }
DEVI void sts128(uint32_t a, uint32_t x, uint32_t y, uint32_t z, uint32_t w) {
  asm volatile("st.shared.v4.u32 [%0],{%1,%2,%3,%4};" ::"r"(a), "r"(x), "r"(y), "r"(z), "r"(w) : "memory");
}
DEVI uint32_t hfma2(uint32_t a, uint32_t b, uint32_t c) { uint32_t d; asm("fma.rn.bf16x2 %0,%1,%2,%3;" : "=r"(d) : "r"(a), "r"(b), "r"(c)); return d; }
DEVI uint32_t hmul2(uint32_t a, uint32_t b) { uint32_t d; asm("mul.rn.bf16x2 %0,%1,%2;" : "=r"(d) : "r"(a), "r"(b)); return d; }
DEVI float ex2(float x) { float y; asm("ex2.approx.ftz.f32 %0,%1;" : "=f"(y) : "f"(x)); return y; }
DEVI float rcp(float x) { float y; asm("rcp.approx.ftz.f32 %0,%1;" : "=f"(y) : "f"(x)); return y; }

__device__ __forceinline__ void conv_mma(float* d, uint32_t da, uint32_t db) {
  asm volatile(
   "{.reg .pred p0,p1; .reg .b64 a,b; .reg .b32 x,y,ha,hb;\n"
   "setp.ne.b32 p0,0,0; setp.eq.b32 p1,0,0; mov.b32 ha,35; mov.b32 hb,8;\n"
   "wgmma.fence.sync.aligned;\n"
   "add.u32 x,%64,0; add.u32 y,%65,0; mov.b64 a,{x,ha}; mov.b64 b,{y,hb};\n"
   "wgmma.mma_async.sync.aligned.m64n128k16.f32.bf16.bf16 {%0,%1,%2,%3,%4,%5,%6,%7,%8,%9,%10,%11,%12,%13,%14,%15,%16,%17,%18,%19,%20,%21,%22,%23,%24,%25,%26,%27,%28,%29,%30,%31,%32,%33,%34,%35,%36,%37,%38,%39,%40,%41,%42,%43,%44,%45,%46,%47,%48,%49,%50,%51,%52,%53,%54,%55,%56,%57,%58,%59,%60,%61,%62,%63},a,b,p0,1,1,0,0;\n"
   "add.u32 x,%64,2; add.u32 y,%65,290; mov.b64 a,{x,ha}; mov.b64 b,{y,hb};\n"
   "wgmma.mma_async.sync.aligned.m64n128k16.f32.bf16.bf16 {%0,%1,%2,%3,%4,%5,%6,%7,%8,%9,%10,%11,%12,%13,%14,%15,%16,%17,%18,%19,%20,%21,%22,%23,%24,%25,%26,%27,%28,%29,%30,%31,%32,%33,%34,%35,%36,%37,%38,%39,%40,%41,%42,%43,%44,%45,%46,%47,%48,%49,%50,%51,%52,%53,%54,%55,%56,%57,%58,%59,%60,%61,%62,%63},a,b,p1,1,1,0,0;\n"
   "add.u32 x,%64,8; add.u32 y,%65,4; mov.b64 a,{x,ha}; mov.b64 b,{y,hb};\n"
   "wgmma.mma_async.sync.aligned.m64n128k16.f32.bf16.bf16 {%0,%1,%2,%3,%4,%5,%6,%7,%8,%9,%10,%11,%12,%13,%14,%15,%16,%17,%18,%19,%20,%21,%22,%23,%24,%25,%26,%27,%28,%29,%30,%31,%32,%33,%34,%35,%36,%37,%38,%39,%40,%41,%42,%43,%44,%45,%46,%47,%48,%49,%50,%51,%52,%53,%54,%55,%56,%57,%58,%59,%60,%61,%62,%63},a,b,p1,1,1,0,0;\n"
   "add.u32 x,%64,10; add.u32 y,%65,294; mov.b64 a,{x,ha}; mov.b64 b,{y,hb};\n"
   "wgmma.mma_async.sync.aligned.m64n128k16.f32.bf16.bf16 {%0,%1,%2,%3,%4,%5,%6,%7,%8,%9,%10,%11,%12,%13,%14,%15,%16,%17,%18,%19,%20,%21,%22,%23,%24,%25,%26,%27,%28,%29,%30,%31,%32,%33,%34,%35,%36,%37,%38,%39,%40,%41,%42,%43,%44,%45,%46,%47,%48,%49,%50,%51,%52,%53,%54,%55,%56,%57,%58,%59,%60,%61,%62,%63},a,b,p1,1,1,0,0;\n"
   "add.u32 x,%64,16; add.u32 y,%65,8; mov.b64 a,{x,ha}; mov.b64 b,{y,hb};\n"
   "wgmma.mma_async.sync.aligned.m64n128k16.f32.bf16.bf16 {%0,%1,%2,%3,%4,%5,%6,%7,%8,%9,%10,%11,%12,%13,%14,%15,%16,%17,%18,%19,%20,%21,%22,%23,%24,%25,%26,%27,%28,%29,%30,%31,%32,%33,%34,%35,%36,%37,%38,%39,%40,%41,%42,%43,%44,%45,%46,%47,%48,%49,%50,%51,%52,%53,%54,%55,%56,%57,%58,%59,%60,%61,%62,%63},a,b,p1,1,1,0,0;\n"
   "add.u32 x,%64,18; add.u32 y,%65,298; mov.b64 a,{x,ha}; mov.b64 b,{y,hb};\n"
   "wgmma.mma_async.sync.aligned.m64n128k16.f32.bf16.bf16 {%0,%1,%2,%3,%4,%5,%6,%7,%8,%9,%10,%11,%12,%13,%14,%15,%16,%17,%18,%19,%20,%21,%22,%23,%24,%25,%26,%27,%28,%29,%30,%31,%32,%33,%34,%35,%36,%37,%38,%39,%40,%41,%42,%43,%44,%45,%46,%47,%48,%49,%50,%51,%52,%53,%54,%55,%56,%57,%58,%59,%60,%61,%62,%63},a,b,p1,1,1,0,0;\n"
   "add.u32 x,%64,24; add.u32 y,%65,12; mov.b64 a,{x,ha}; mov.b64 b,{y,hb};\n"
   "wgmma.mma_async.sync.aligned.m64n128k16.f32.bf16.bf16 {%0,%1,%2,%3,%4,%5,%6,%7,%8,%9,%10,%11,%12,%13,%14,%15,%16,%17,%18,%19,%20,%21,%22,%23,%24,%25,%26,%27,%28,%29,%30,%31,%32,%33,%34,%35,%36,%37,%38,%39,%40,%41,%42,%43,%44,%45,%46,%47,%48,%49,%50,%51,%52,%53,%54,%55,%56,%57,%58,%59,%60,%61,%62,%63},a,b,p1,1,1,0,0;\n"
   "add.u32 x,%64,26; add.u32 y,%65,302; mov.b64 a,{x,ha}; mov.b64 b,{y,hb};\n"
   "wgmma.mma_async.sync.aligned.m64n128k16.f32.bf16.bf16 {%0,%1,%2,%3,%4,%5,%6,%7,%8,%9,%10,%11,%12,%13,%14,%15,%16,%17,%18,%19,%20,%21,%22,%23,%24,%25,%26,%27,%28,%29,%30,%31,%32,%33,%34,%35,%36,%37,%38,%39,%40,%41,%42,%43,%44,%45,%46,%47,%48,%49,%50,%51,%52,%53,%54,%55,%56,%57,%58,%59,%60,%61,%62,%63},a,b,p1,1,1,0,0;\n"
   "wgmma.commit_group.sync.aligned;\n"
   "wgmma.wait_group.sync.aligned 0;\n"
   "add.u32 x,%64,280; add.u32 y,%65,32; mov.b64 a,{x,ha}; mov.b64 b,{y,hb};\n"
   "wgmma.mma_async.sync.aligned.m64n96k16.f32.bf16.bf16 {%0,%1,%2,%3,%4,%5,%6,%7,%8,%9,%10,%11,%12,%13,%14,%15,%16,%17,%18,%19,%20,%21,%22,%23,%24,%25,%26,%27,%28,%29,%30,%31,%32,%33,%34,%35,%36,%37,%38,%39,%40,%41,%42,%43,%44,%45,%46,%47},a,b,p1,1,1,0,0;\n"
   "add.u32 x,%64,282; add.u32 y,%65,322; mov.b64 a,{x,ha}; mov.b64 b,{y,hb};\n"
   "wgmma.mma_async.sync.aligned.m64n96k16.f32.bf16.bf16 {%0,%1,%2,%3,%4,%5,%6,%7,%8,%9,%10,%11,%12,%13,%14,%15,%16,%17,%18,%19,%20,%21,%22,%23,%24,%25,%26,%27,%28,%29,%30,%31,%32,%33,%34,%35,%36,%37,%38,%39,%40,%41,%42,%43,%44,%45,%46,%47},a,b,p1,1,1,0,0;\n"
   "add.u32 x,%64,288; add.u32 y,%65,36; mov.b64 a,{x,ha}; mov.b64 b,{y,hb};\n"
   "wgmma.mma_async.sync.aligned.m64n96k16.f32.bf16.bf16 {%0,%1,%2,%3,%4,%5,%6,%7,%8,%9,%10,%11,%12,%13,%14,%15,%16,%17,%18,%19,%20,%21,%22,%23,%24,%25,%26,%27,%28,%29,%30,%31,%32,%33,%34,%35,%36,%37,%38,%39,%40,%41,%42,%43,%44,%45,%46,%47},a,b,p1,1,1,0,0;\n"
   "add.u32 x,%64,290; add.u32 y,%65,326; mov.b64 a,{x,ha}; mov.b64 b,{y,hb};\n"
   "wgmma.mma_async.sync.aligned.m64n96k16.f32.bf16.bf16 {%0,%1,%2,%3,%4,%5,%6,%7,%8,%9,%10,%11,%12,%13,%14,%15,%16,%17,%18,%19,%20,%21,%22,%23,%24,%25,%26,%27,%28,%29,%30,%31,%32,%33,%34,%35,%36,%37,%38,%39,%40,%41,%42,%43,%44,%45,%46,%47},a,b,p1,1,1,0,0;\n"
   "add.u32 x,%64,296; add.u32 y,%65,40; mov.b64 a,{x,ha}; mov.b64 b,{y,hb};\n"
   "wgmma.mma_async.sync.aligned.m64n96k16.f32.bf16.bf16 {%0,%1,%2,%3,%4,%5,%6,%7,%8,%9,%10,%11,%12,%13,%14,%15,%16,%17,%18,%19,%20,%21,%22,%23,%24,%25,%26,%27,%28,%29,%30,%31,%32,%33,%34,%35,%36,%37,%38,%39,%40,%41,%42,%43,%44,%45,%46,%47},a,b,p1,1,1,0,0;\n"
   "add.u32 x,%64,298; add.u32 y,%65,330; mov.b64 a,{x,ha}; mov.b64 b,{y,hb};\n"
   "wgmma.mma_async.sync.aligned.m64n96k16.f32.bf16.bf16 {%0,%1,%2,%3,%4,%5,%6,%7,%8,%9,%10,%11,%12,%13,%14,%15,%16,%17,%18,%19,%20,%21,%22,%23,%24,%25,%26,%27,%28,%29,%30,%31,%32,%33,%34,%35,%36,%37,%38,%39,%40,%41,%42,%43,%44,%45,%46,%47},a,b,p1,1,1,0,0;\n"
   "add.u32 x,%64,304; add.u32 y,%65,44; mov.b64 a,{x,ha}; mov.b64 b,{y,hb};\n"
   "wgmma.mma_async.sync.aligned.m64n96k16.f32.bf16.bf16 {%0,%1,%2,%3,%4,%5,%6,%7,%8,%9,%10,%11,%12,%13,%14,%15,%16,%17,%18,%19,%20,%21,%22,%23,%24,%25,%26,%27,%28,%29,%30,%31,%32,%33,%34,%35,%36,%37,%38,%39,%40,%41,%42,%43,%44,%45,%46,%47},a,b,p1,1,1,0,0;\n"
   "add.u32 x,%64,306; add.u32 y,%65,334; mov.b64 a,{x,ha}; mov.b64 b,{y,hb};\n"
   "wgmma.mma_async.sync.aligned.m64n96k16.f32.bf16.bf16 {%0,%1,%2,%3,%4,%5,%6,%7,%8,%9,%10,%11,%12,%13,%14,%15,%16,%17,%18,%19,%20,%21,%22,%23,%24,%25,%26,%27,%28,%29,%30,%31,%32,%33,%34,%35,%36,%37,%38,%39,%40,%41,%42,%43,%44,%45,%46,%47},a,b,p1,1,1,0,0;\n"
   "wgmma.commit_group.sync.aligned;\n"
   "wgmma.wait_group.sync.aligned 0;\n"
   "add.u32 x,%64,560; add.u32 y,%65,64; mov.b64 a,{x,ha}; mov.b64 b,{y,hb};\n"
   "wgmma.mma_async.sync.aligned.m64n64k16.f32.bf16.bf16 {%0,%1,%2,%3,%4,%5,%6,%7,%8,%9,%10,%11,%12,%13,%14,%15,%16,%17,%18,%19,%20,%21,%22,%23,%24,%25,%26,%27,%28,%29,%30,%31},a,b,p1,1,1,0,0;\n"
   "add.u32 x,%64,562; add.u32 y,%65,354; mov.b64 a,{x,ha}; mov.b64 b,{y,hb};\n"
   "wgmma.mma_async.sync.aligned.m64n64k16.f32.bf16.bf16 {%0,%1,%2,%3,%4,%5,%6,%7,%8,%9,%10,%11,%12,%13,%14,%15,%16,%17,%18,%19,%20,%21,%22,%23,%24,%25,%26,%27,%28,%29,%30,%31},a,b,p1,1,1,0,0;\n"
   "add.u32 x,%64,568; add.u32 y,%65,68; mov.b64 a,{x,ha}; mov.b64 b,{y,hb};\n"
   "wgmma.mma_async.sync.aligned.m64n64k16.f32.bf16.bf16 {%0,%1,%2,%3,%4,%5,%6,%7,%8,%9,%10,%11,%12,%13,%14,%15,%16,%17,%18,%19,%20,%21,%22,%23,%24,%25,%26,%27,%28,%29,%30,%31},a,b,p1,1,1,0,0;\n"
   "add.u32 x,%64,570; add.u32 y,%65,358; mov.b64 a,{x,ha}; mov.b64 b,{y,hb};\n"
   "wgmma.mma_async.sync.aligned.m64n64k16.f32.bf16.bf16 {%0,%1,%2,%3,%4,%5,%6,%7,%8,%9,%10,%11,%12,%13,%14,%15,%16,%17,%18,%19,%20,%21,%22,%23,%24,%25,%26,%27,%28,%29,%30,%31},a,b,p1,1,1,0,0;\n"
   "add.u32 x,%64,576; add.u32 y,%65,72; mov.b64 a,{x,ha}; mov.b64 b,{y,hb};\n"
   "wgmma.mma_async.sync.aligned.m64n64k16.f32.bf16.bf16 {%0,%1,%2,%3,%4,%5,%6,%7,%8,%9,%10,%11,%12,%13,%14,%15,%16,%17,%18,%19,%20,%21,%22,%23,%24,%25,%26,%27,%28,%29,%30,%31},a,b,p1,1,1,0,0;\n"
   "add.u32 x,%64,578; add.u32 y,%65,362; mov.b64 a,{x,ha}; mov.b64 b,{y,hb};\n"
   "wgmma.mma_async.sync.aligned.m64n64k16.f32.bf16.bf16 {%0,%1,%2,%3,%4,%5,%6,%7,%8,%9,%10,%11,%12,%13,%14,%15,%16,%17,%18,%19,%20,%21,%22,%23,%24,%25,%26,%27,%28,%29,%30,%31},a,b,p1,1,1,0,0;\n"
   "add.u32 x,%64,584; add.u32 y,%65,76; mov.b64 a,{x,ha}; mov.b64 b,{y,hb};\n"
   "wgmma.mma_async.sync.aligned.m64n64k16.f32.bf16.bf16 {%0,%1,%2,%3,%4,%5,%6,%7,%8,%9,%10,%11,%12,%13,%14,%15,%16,%17,%18,%19,%20,%21,%22,%23,%24,%25,%26,%27,%28,%29,%30,%31},a,b,p1,1,1,0,0;\n"
   "add.u32 x,%64,586; add.u32 y,%65,366; mov.b64 a,{x,ha}; mov.b64 b,{y,hb};\n"
   "wgmma.mma_async.sync.aligned.m64n64k16.f32.bf16.bf16 {%0,%1,%2,%3,%4,%5,%6,%7,%8,%9,%10,%11,%12,%13,%14,%15,%16,%17,%18,%19,%20,%21,%22,%23,%24,%25,%26,%27,%28,%29,%30,%31},a,b,p1,1,1,0,0;\n"
   "wgmma.commit_group.sync.aligned;\n"
   "wgmma.wait_group.sync.aligned 0;\n"
   "add.u32 x,%64,840; add.u32 y,%65,96; mov.b64 a,{x,ha}; mov.b64 b,{y,hb};\n"
   "wgmma.mma_async.sync.aligned.m64n32k16.f32.bf16.bf16 {%0,%1,%2,%3,%4,%5,%6,%7,%8,%9,%10,%11,%12,%13,%14,%15},a,b,p1,1,1,0,0;\n"
   "add.u32 x,%64,842; add.u32 y,%65,386; mov.b64 a,{x,ha}; mov.b64 b,{y,hb};\n"
   "wgmma.mma_async.sync.aligned.m64n32k16.f32.bf16.bf16 {%0,%1,%2,%3,%4,%5,%6,%7,%8,%9,%10,%11,%12,%13,%14,%15},a,b,p1,1,1,0,0;\n"
   "add.u32 x,%64,848; add.u32 y,%65,100; mov.b64 a,{x,ha}; mov.b64 b,{y,hb};\n"
   "wgmma.mma_async.sync.aligned.m64n32k16.f32.bf16.bf16 {%0,%1,%2,%3,%4,%5,%6,%7,%8,%9,%10,%11,%12,%13,%14,%15},a,b,p1,1,1,0,0;\n"
   "add.u32 x,%64,850; add.u32 y,%65,390; mov.b64 a,{x,ha}; mov.b64 b,{y,hb};\n"
   "wgmma.mma_async.sync.aligned.m64n32k16.f32.bf16.bf16 {%0,%1,%2,%3,%4,%5,%6,%7,%8,%9,%10,%11,%12,%13,%14,%15},a,b,p1,1,1,0,0;\n"
   "add.u32 x,%64,856; add.u32 y,%65,104; mov.b64 a,{x,ha}; mov.b64 b,{y,hb};\n"
   "wgmma.mma_async.sync.aligned.m64n32k16.f32.bf16.bf16 {%0,%1,%2,%3,%4,%5,%6,%7,%8,%9,%10,%11,%12,%13,%14,%15},a,b,p1,1,1,0,0;\n"
   "add.u32 x,%64,858; add.u32 y,%65,394; mov.b64 a,{x,ha}; mov.b64 b,{y,hb};\n"
   "wgmma.mma_async.sync.aligned.m64n32k16.f32.bf16.bf16 {%0,%1,%2,%3,%4,%5,%6,%7,%8,%9,%10,%11,%12,%13,%14,%15},a,b,p1,1,1,0,0;\n"
   "add.u32 x,%64,864; add.u32 y,%65,108; mov.b64 a,{x,ha}; mov.b64 b,{y,hb};\n"
   "wgmma.mma_async.sync.aligned.m64n32k16.f32.bf16.bf16 {%0,%1,%2,%3,%4,%5,%6,%7,%8,%9,%10,%11,%12,%13,%14,%15},a,b,p1,1,1,0,0;\n"
   "add.u32 x,%64,866; add.u32 y,%65,398; mov.b64 a,{x,ha}; mov.b64 b,{y,hb};\n"
   "wgmma.mma_async.sync.aligned.m64n32k16.f32.bf16.bf16 {%0,%1,%2,%3,%4,%5,%6,%7,%8,%9,%10,%11,%12,%13,%14,%15},a,b,p1,1,1,0,0;\n"
   "wgmma.commit_group.sync.aligned;\n"
   "wgmma.wait_group.sync.aligned 0;\n"
   "}\n"
   :"=f"(d[0]),"=f"(d[1]),"=f"(d[2]),"=f"(d[3]),"=f"(d[4]),"=f"(d[5]),"=f"(d[6]),"=f"(d[7]),"=f"(d[8]),"=f"(d[9]),"=f"(d[10]),"=f"(d[11]),"=f"(d[12]),"=f"(d[13]),"=f"(d[14]),"=f"(d[15]),"=f"(d[16]),"=f"(d[17]),"=f"(d[18]),"=f"(d[19]),"=f"(d[20]),"=f"(d[21]),"=f"(d[22]),"=f"(d[23]),"=f"(d[24]),"=f"(d[25]),"=f"(d[26]),"=f"(d[27]),"=f"(d[28]),"=f"(d[29]),"=f"(d[30]),"=f"(d[31]),"=f"(d[32]),"=f"(d[33]),"=f"(d[34]),"=f"(d[35]),"=f"(d[36]),"=f"(d[37]),"=f"(d[38]),"=f"(d[39]),"=f"(d[40]),"=f"(d[41]),"=f"(d[42]),"=f"(d[43]),"=f"(d[44]),"=f"(d[45]),"=f"(d[46]),"=f"(d[47]),"=f"(d[48]),"=f"(d[49]),"=f"(d[50]),"=f"(d[51]),"=f"(d[52]),"=f"(d[53]),"=f"(d[54]),"=f"(d[55]),"=f"(d[56]),"=f"(d[57]),"=f"(d[58]),"=f"(d[59]),"=f"(d[60]),"=f"(d[61]),"=f"(d[62]),"=f"(d[63])
   :"r"(da),"r"(db):"memory");
}

__device__ __forceinline__ void wg0_n144(float* d, uint64_t da, uint64_t db, int) {
  asm volatile("{.reg .pred p; setp.ne.b32 p,0,0;\n"
   "wgmma.mma_async.sync.aligned.m64n144k16.f32.bf16.bf16 {%0,%1,%2,%3,%4,%5,%6,%7,%8,%9,%10,%11,%12,%13,%14,%15,%16,%17,%18,%19,%20,%21,%22,%23,%24,%25,%26,%27,%28,%29,%30,%31,%32,%33,%34,%35,%36,%37,%38,%39,%40,%41,%42,%43,%44,%45,%46,%47,%48,%49,%50,%51,%52,%53,%54,%55,%56,%57,%58,%59,%60,%61,%62,%63,%64,%65,%66,%67,%68,%69,%70,%71},%72,%73,p,1,1,1,0;}"
   :"=f"(d[0]),"=f"(d[1]),"=f"(d[2]),"=f"(d[3]),"=f"(d[4]),"=f"(d[5]),"=f"(d[6]),"=f"(d[7]),"=f"(d[8]),"=f"(d[9]),"=f"(d[10]),"=f"(d[11]),"=f"(d[12]),"=f"(d[13]),"=f"(d[14]),"=f"(d[15]),"=f"(d[16]),"=f"(d[17]),"=f"(d[18]),"=f"(d[19]),"=f"(d[20]),"=f"(d[21]),"=f"(d[22]),"=f"(d[23]),"=f"(d[24]),"=f"(d[25]),"=f"(d[26]),"=f"(d[27]),"=f"(d[28]),"=f"(d[29]),"=f"(d[30]),"=f"(d[31]),"=f"(d[32]),"=f"(d[33]),"=f"(d[34]),"=f"(d[35]),"=f"(d[36]),"=f"(d[37]),"=f"(d[38]),"=f"(d[39]),"=f"(d[40]),"=f"(d[41]),"=f"(d[42]),"=f"(d[43]),"=f"(d[44]),"=f"(d[45]),"=f"(d[46]),"=f"(d[47]),"=f"(d[48]),"=f"(d[49]),"=f"(d[50]),"=f"(d[51]),"=f"(d[52]),"=f"(d[53]),"=f"(d[54]),"=f"(d[55]),"=f"(d[56]),"=f"(d[57]),"=f"(d[58]),"=f"(d[59]),"=f"(d[60]),"=f"(d[61]),"=f"(d[62]),"=f"(d[63]),"=f"(d[64]),"=f"(d[65]),"=f"(d[66]),"=f"(d[67]),"=f"(d[68]),"=f"(d[69]),"=f"(d[70]),"=f"(d[71])
   :"l"(da),"l"(db));
}
__device__ __forceinline__ void wg0_n152(float* d, uint64_t da, uint64_t db, int) {
  asm volatile("{.reg .pred p; setp.ne.b32 p,0,0;\n"
   "wgmma.mma_async.sync.aligned.m64n152k16.f32.bf16.bf16 {%0,%1,%2,%3,%4,%5,%6,%7,%8,%9,%10,%11,%12,%13,%14,%15,%16,%17,%18,%19,%20,%21,%22,%23,%24,%25,%26,%27,%28,%29,%30,%31,%32,%33,%34,%35,%36,%37,%38,%39,%40,%41,%42,%43,%44,%45,%46,%47,%48,%49,%50,%51,%52,%53,%54,%55,%56,%57,%58,%59,%60,%61,%62,%63,%64,%65,%66,%67,%68,%69,%70,%71,%72,%73,%74,%75},%76,%77,p,1,1,1,0;}"
   :"=f"(d[0]),"=f"(d[1]),"=f"(d[2]),"=f"(d[3]),"=f"(d[4]),"=f"(d[5]),"=f"(d[6]),"=f"(d[7]),"=f"(d[8]),"=f"(d[9]),"=f"(d[10]),"=f"(d[11]),"=f"(d[12]),"=f"(d[13]),"=f"(d[14]),"=f"(d[15]),"=f"(d[16]),"=f"(d[17]),"=f"(d[18]),"=f"(d[19]),"=f"(d[20]),"=f"(d[21]),"=f"(d[22]),"=f"(d[23]),"=f"(d[24]),"=f"(d[25]),"=f"(d[26]),"=f"(d[27]),"=f"(d[28]),"=f"(d[29]),"=f"(d[30]),"=f"(d[31]),"=f"(d[32]),"=f"(d[33]),"=f"(d[34]),"=f"(d[35]),"=f"(d[36]),"=f"(d[37]),"=f"(d[38]),"=f"(d[39]),"=f"(d[40]),"=f"(d[41]),"=f"(d[42]),"=f"(d[43]),"=f"(d[44]),"=f"(d[45]),"=f"(d[46]),"=f"(d[47]),"=f"(d[48]),"=f"(d[49]),"=f"(d[50]),"=f"(d[51]),"=f"(d[52]),"=f"(d[53]),"=f"(d[54]),"=f"(d[55]),"=f"(d[56]),"=f"(d[57]),"=f"(d[58]),"=f"(d[59]),"=f"(d[60]),"=f"(d[61]),"=f"(d[62]),"=f"(d[63]),"=f"(d[64]),"=f"(d[65]),"=f"(d[66]),"=f"(d[67]),"=f"(d[68]),"=f"(d[69]),"=f"(d[70]),"=f"(d[71]),"=f"(d[72]),"=f"(d[73]),"=f"(d[74]),"=f"(d[75])
   :"l"(da),"l"(db));
}

__device__ __forceinline__ void wg_n72(float* d, uint64_t da, uint64_t db, int sd) {
  asm volatile("{.reg .pred p; setp.ne.b32 p,%38,0;\n"
   "wgmma.mma_async.sync.aligned.m64n72k16.f32.bf16.bf16 {%0,%1,%2,%3,%4,%5,%6,%7,%8,%9,%10,%11,%12,%13,%14,%15,%16,%17,%18,%19,%20,%21,%22,%23,%24,%25,%26,%27,%28,%29,%30,%31,%32,%33,%34,%35},%36,%37,p,1,1,1,0;}"
   :"+f"(d[0]),"+f"(d[1]),"+f"(d[2]),"+f"(d[3]),"+f"(d[4]),"+f"(d[5]),"+f"(d[6]),"+f"(d[7]),"+f"(d[8]),"+f"(d[9]),"+f"(d[10]),"+f"(d[11]),"+f"(d[12]),"+f"(d[13]),"+f"(d[14]),"+f"(d[15]),"+f"(d[16]),"+f"(d[17]),"+f"(d[18]),"+f"(d[19]),"+f"(d[20]),"+f"(d[21]),"+f"(d[22]),"+f"(d[23]),"+f"(d[24]),"+f"(d[25]),"+f"(d[26]),"+f"(d[27]),"+f"(d[28]),"+f"(d[29]),"+f"(d[30]),"+f"(d[31]),"+f"(d[32]),"+f"(d[33]),"+f"(d[34]),"+f"(d[35])
   :"l"(da),"l"(db),"r"(sd));
}
__device__ __forceinline__ void wg_n144(float* d, uint64_t da, uint64_t db, int sd) {
  asm volatile("{.reg .pred p; setp.ne.b32 p,%74,0;\n"
   "wgmma.mma_async.sync.aligned.m64n144k16.f32.bf16.bf16 {%0,%1,%2,%3,%4,%5,%6,%7,%8,%9,%10,%11,%12,%13,%14,%15,%16,%17,%18,%19,%20,%21,%22,%23,%24,%25,%26,%27,%28,%29,%30,%31,%32,%33,%34,%35,%36,%37,%38,%39,%40,%41,%42,%43,%44,%45,%46,%47,%48,%49,%50,%51,%52,%53,%54,%55,%56,%57,%58,%59,%60,%61,%62,%63,%64,%65,%66,%67,%68,%69,%70,%71},%72,%73,p,1,1,1,0;}"
   :"+f"(d[0]),"+f"(d[1]),"+f"(d[2]),"+f"(d[3]),"+f"(d[4]),"+f"(d[5]),"+f"(d[6]),"+f"(d[7]),"+f"(d[8]),"+f"(d[9]),"+f"(d[10]),"+f"(d[11]),"+f"(d[12]),"+f"(d[13]),"+f"(d[14]),"+f"(d[15]),"+f"(d[16]),"+f"(d[17]),"+f"(d[18]),"+f"(d[19]),"+f"(d[20]),"+f"(d[21]),"+f"(d[22]),"+f"(d[23]),"+f"(d[24]),"+f"(d[25]),"+f"(d[26]),"+f"(d[27]),"+f"(d[28]),"+f"(d[29]),"+f"(d[30]),"+f"(d[31]),"+f"(d[32]),"+f"(d[33]),"+f"(d[34]),"+f"(d[35]),"+f"(d[36]),"+f"(d[37]),"+f"(d[38]),"+f"(d[39]),"+f"(d[40]),"+f"(d[41]),"+f"(d[42]),"+f"(d[43]),"+f"(d[44]),"+f"(d[45]),"+f"(d[46]),"+f"(d[47]),"+f"(d[48]),"+f"(d[49]),"+f"(d[50]),"+f"(d[51]),"+f"(d[52]),"+f"(d[53]),"+f"(d[54]),"+f"(d[55]),"+f"(d[56]),"+f"(d[57]),"+f"(d[58]),"+f"(d[59]),"+f"(d[60]),"+f"(d[61]),"+f"(d[62]),"+f"(d[63]),"+f"(d[64]),"+f"(d[65]),"+f"(d[66]),"+f"(d[67]),"+f"(d[68]),"+f"(d[69]),"+f"(d[70]),"+f"(d[71])
   :"l"(da),"l"(db),"r"(sd));
}
__device__ __forceinline__ void wg_n152(float* d, uint64_t da, uint64_t db, int sd) {
  asm volatile("{.reg .pred p; setp.ne.b32 p,%78,0;\n"
   "wgmma.mma_async.sync.aligned.m64n152k16.f32.bf16.bf16 {%0,%1,%2,%3,%4,%5,%6,%7,%8,%9,%10,%11,%12,%13,%14,%15,%16,%17,%18,%19,%20,%21,%22,%23,%24,%25,%26,%27,%28,%29,%30,%31,%32,%33,%34,%35,%36,%37,%38,%39,%40,%41,%42,%43,%44,%45,%46,%47,%48,%49,%50,%51,%52,%53,%54,%55,%56,%57,%58,%59,%60,%61,%62,%63,%64,%65,%66,%67,%68,%69,%70,%71,%72,%73,%74,%75},%76,%77,p,1,1,1,0;}"
   :"+f"(d[0]),"+f"(d[1]),"+f"(d[2]),"+f"(d[3]),"+f"(d[4]),"+f"(d[5]),"+f"(d[6]),"+f"(d[7]),"+f"(d[8]),"+f"(d[9]),"+f"(d[10]),"+f"(d[11]),"+f"(d[12]),"+f"(d[13]),"+f"(d[14]),"+f"(d[15]),"+f"(d[16]),"+f"(d[17]),"+f"(d[18]),"+f"(d[19]),"+f"(d[20]),"+f"(d[21]),"+f"(d[22]),"+f"(d[23]),"+f"(d[24]),"+f"(d[25]),"+f"(d[26]),"+f"(d[27]),"+f"(d[28]),"+f"(d[29]),"+f"(d[30]),"+f"(d[31]),"+f"(d[32]),"+f"(d[33]),"+f"(d[34]),"+f"(d[35]),"+f"(d[36]),"+f"(d[37]),"+f"(d[38]),"+f"(d[39]),"+f"(d[40]),"+f"(d[41]),"+f"(d[42]),"+f"(d[43]),"+f"(d[44]),"+f"(d[45]),"+f"(d[46]),"+f"(d[47]),"+f"(d[48]),"+f"(d[49]),"+f"(d[50]),"+f"(d[51]),"+f"(d[52]),"+f"(d[53]),"+f"(d[54]),"+f"(d[55]),"+f"(d[56]),"+f"(d[57]),"+f"(d[58]),"+f"(d[59]),"+f"(d[60]),"+f"(d[61]),"+f"(d[62]),"+f"(d[63]),"+f"(d[64]),"+f"(d[65]),"+f"(d[66]),"+f"(d[67]),"+f"(d[68]),"+f"(d[69]),"+f"(d[70]),"+f"(d[71]),"+f"(d[72]),"+f"(d[73]),"+f"(d[74]),"+f"(d[75])
   :"l"(da),"l"(db),"r"(sd));
}

template <int N> DEVI void fence_regs(float* d) {
#pragma unroll
  for (int i = 0; i < N; i++) asm volatile("" : "+f"(d[i])::"memory");
}
template <int N> DEVI void wg_mma(float* d, uint64_t da, uint64_t db, int sd) {
  if constexpr (N == 72) wg_n72(d, da, db, sd);
  if constexpr (N == 144) wg_n144(d, da, db, sd);
  if constexpr (N == 152) wg_n152(d, da, db, sd);
}

struct KvRegs { uint32_t u[8][2]; };
struct KvAddr { uint32_t k[11], v, t; };
DEVI void kv_addr(KvAddr& ad, int lane) {
  const int a = lane >> 1;
  const uint32_t hf = (lane & 1) * 8;
#pragma unroll
  for (int i = 0; i < 11; i++) {
    const int row = i < 3 ? (5 + i) * 17 + a : (i - 3) * 17 + a + 1;
    ad.k[i] = pin(row * 64 + (((row >> 1) & 3) << 4) + hf);
  }
  ad.v = pin(KIN + a * 64 + (((a >> 1) & 3) << 4) + hf);
  ad.t = pin(KIN + VIN + hf * 4);
}
DEVI void kv_load(uint32_t buf, const CUtensorMap* tmK, const CUtensorMap* tmV, const __nv_bfloat16* shp, int ch, int rc, uint32_t bar) {
  tma3d(buf, tmK, ch, rc * 16 - 1, 0, bar);
  tma3d(buf + KIN, tmV, ch, rc * 16, 0, bar);
  bulk_load(buf + KIN + VIN, shp + ch * 4, 256, bar);
}
DEVI void kv_compute(KvRegs& o, const KvAddr& ad, uint32_t buf, int col) {
  uint2 kr[11], vr[8];
#pragma unroll
  for (int i = 0; i < 11; i++)
    asm volatile("ld.shared.v2.u32 {%0,%1},[%2];" : "=r"(kr[i].x), "=r"(kr[i].y) : "r"(buf + (ad.k[i] ^ (col << 4))) : "memory");
  const uint4 w0 = lds128(buf + ad.t + col * 64), w1 = lds128(buf + ad.t + col * 64 + 16);
#pragma unroll
  for (int i = 0; i < 8; i++)
    asm volatile("ld.shared.v2.u32 {%0,%1},[%2];" : "=r"(vr[i].x), "=r"(vr[i].y) : "r"(buf + (ad.v ^ (col << 4)) + i * 1024) : "memory");
  const uint32_t t0 = __byte_perm(w0.x, w0.z, 0x5410), t1 = __byte_perm(w0.x, w0.z, 0x7632), t2 = __byte_perm(w0.y, w0.w, 0x5410),
                 t3 = __byte_perm(w0.y, w0.w, 0x7632), s0 = __byte_perm(w1.x, w1.z, 0x5410), s1 = __byte_perm(w1.x, w1.z, 0x7632),
                 s2 = __byte_perm(w1.y, w1.w, 0x5410), s3 = __byte_perm(w1.y, w1.w, 0x7632);
#pragma unroll
  for (int i = 0; i < 8; i++) {
    o.u[i][0] = hmul2(hfma2(kr[i + 3].x, t0, hfma2(kr[i + 2].x, t1, hfma2(kr[i + 1].x, t2, hmul2(kr[i].x, t3)))), vr[i].x);
    o.u[i][1] = hmul2(hfma2(kr[i + 3].y, s0, hfma2(kr[i + 2].y, s1, hfma2(kr[i + 1].y, s2, hmul2(kr[i].y, s3)))), vr[i].y);
  }
}
DEVI uint4 kv_pack(const KvRegs& o, int ch) {
  const uint32_t sel = (ch & 1) ? 0x7632 : 0x5410;
  const int cp = ch >> 1;
  return make_uint4(__byte_perm(o.u[7][cp], o.u[6][cp], sel), __byte_perm(o.u[5][cp], o.u[4][cp], sel),
                    __byte_perm(o.u[3][cp], o.u[2][cp], sel), __byte_perm(o.u[1][cp], o.u[0][cp], sel));
}
DEVI void kv_store(const KvRegs& o, int ch8, int rc, int lane) {
  uint4* dst = (uint4*)g_U + (size_t)(ch8 + (lane & 1) * 4) * 256 + (255 - rc * 16 - (lane >> 1));
#pragma unroll
  for (int ch = 0; ch < 4; ch++) __stcg(dst + ch * 256, kv_pack(o, ch));
}
DEVI void kv_publish(int lane) {
  asm volatile("fence.acq_rel.gpu;" ::: "memory");
  __syncwarp();
  if (lane == 0) asm volatile("red.relaxed.gpu.global.add.u32 [%0],%1;" ::"l"(&g_ucnt), "r"(1u) : "memory");
}

template <int NT_> struct HRegs { static constexpr int K = (280 + NT_ - 1) / NT_; uint4 A[K], B[K]; uint32_t d; };
template <int NT_>
DEVI void conv_load_h(HRegs<NT_>& r, const __nv_bfloat16* h, const __nv_bfloat16* dp, int tid, bool act = true) {
  r.d = 0;
  if (act) r.d = *(const unsigned short*)dp;
#pragma unroll
  for (int k = 0; k < HRegs<NT_>::K; k++) r.A[k] = r.B[k] = make_uint4(0, 0, 0, 0);
  if (act) {
#pragma unroll
    for (int k = 0; k < HRegs<NT_>::K; k++) {
      const int idx = min(tid + NT_ * k, 279), m = (idx * 1873) >> 16, z = idx - 3 * m - 4;
      const uint4* p = (const uint4*)h + z;
      if (k > 0 || z >= 0) r.A[k] = __ldg(p);
      if (k > 0 || z >= -1) r.B[k] = __ldg(p + 1);
    }
  }
}
template <int NT_>
DEVI void conv_expand_h(const HRegs<NT_>& r, uint32_t hs, int tid) {
#pragma unroll
  for (int k = 0; k < HRegs<NT_>::K; k++) {
    const int idx = tid + NT_ * k, m = (idx * 1873) >> 16;
    const uint32_t a = hs + idx * 16 + (m >> 1) * (4480 - 2 * HCP);
    const uint4 A = r.A[k];
    uint4 B = r.B[k];
    if (k == 0 && tid == 3) B.x = __byte_perm(pack2(bflo(B.x) + bflo(r.d), 0.f), B.x, 0x7610);
    if (idx < 280) {
      sts128(a, A.y, A.z, A.w, B.x);
      sts128(a + 2 * HCP, A.z, A.w, B.x, B.y);
      sts128(a + 4 * HCP, A.w, B.x, B.y, B.z);
      sts128(a + 6 * HCP, B.x, B.y, B.z, B.w);
      if (A.x == 0xffffffffu) sts32(a, A.y);
    }
  }
}
struct URegs { uint4 v[2]; uint32_t n[2]; };
DEVI int u_chunk(int tid) { return (tid & 0x70) | ((tid & 3) << 2) | ((tid >> 2) & 3); }
DEVI void conv_load_u(URegs& r, const __nv_bfloat16* u, int tid) {
  const int z = u_chunk(tid);
  r.v[0] = __ldcg((const uint4*)u + z);
  r.v[1] = __ldcg((const uint4*)u + z + 128);
  r.n[0] = __ldcg((const uint32_t*)u + 4 * z + 4);
  r.n[1] = z == 127 ? 0u : __ldcg((const uint32_t*)u + 4 * z + 516);
}
DEVI void conv_load_u_smem(URegs& r, uint32_t u, int tid) {
  const uint32_t a = u + u_chunk(tid) * 16;
  r.v[0] = lds128(a);
  r.v[1] = lds128(a + 2048);
  r.n[0] = lds32(a + 16);
  r.n[1] = u_chunk(tid) == 127 ? 0u : lds32(a + 2064);
}
DEVI void conv_build_u(const URegs& r, uint32_t us, int tid) {
  const int z = u_chunk(tid);
  const uint32_t a = us + (z & 3) * UAP + (z >> 2) * 32;
#pragma unroll
  for (int k = 0; k < 2; k++) {
    const uint4 v = r.v[k];
    sts128(a + k * 1024, __funnelshift_r(v.x, v.y, 16), __funnelshift_r(v.y, v.z, 16), __funnelshift_r(v.z, v.w, 16),
           __funnelshift_r(v.w, r.n[k], 16));
    sts128(a + k * 1024 + 16, v.x, v.y, v.z, v.w);
  }
  if (tid < 64) sts128(us + (tid >> 4) * UAP + 2048 + (tid & 15) * 16, 0, 0, 0, 0);
}
DEVI void conv_channel(uint32_t hs, uint32_t us, uint32_t ys, int barid, int w, int lane, uint32_t donebar) {
  static_assert(HCP == 560 && UAP == 2320, "conv_mma has the table pitches built in");
  float acc[64];
  conv_mma(acc, ((hs & 0x3FFFF) >> 4) | (1u << 16), ((us & 0x3FFFF) >> 4) | ((uint32_t)(UAP >> 4) << 16));
  if (donebar && lane == 0) mbar_arrive_n(donebar, 2);
  bar_sync(barid, 128);
  const int t = lane & 3;
  const bool q = lane & 16, up = !q && t == 3, dn = q && t == 0;
  const int src = ((lane ^ 16) & 28) | ((q ? t + 3 : t + 1) & 3);
  float keep[16], recv[16];
#pragma unroll
  for (int j = 0; j < 16; j++) {
    const float e0 = j < 14 ? acc[4 * j] + acc[4 * j + 10] : acc[4 * j], e1 = j < 14 ? acc[4 * j + 1] + acc[4 * j + 11] : acc[4 * j + 1];
    keep[j] = q ? e1 : e0;
    recv[j] = __shfl_sync(~0u, q ? e0 : e1, src);
  }
  const uint32_t a = ys + (q ? 2048 + 32 : 0) + (63 - t) * 32 + ((lane >> 2) & 3) * 8 + w * 2;
#pragma unroll
  for (int j = 0; j < 16; j += 2) {
    float v0 = up ? recv[j + 1] : recv[j], v1 = up ? (j + 2 < 16 ? recv[j + 2] : 0.f) : recv[j + 1];
    v0 = dn ? recv[(j + 15) & 15] : v0;
    v1 = dn ? recv[j] : v1;
    v0 += (j == 0 && dn) ? 0.f : keep[j];
    const uint32_t p = pack2(v0, v1 + keep[j + 1]);
    sts16((j == 0 && dn) ? a - 2048 : a - j * 128, p);
    sts16(a - j * 128 - 128, p >> 16);
  }
}

constexpr int SMEM_SIDE = 4 * (18432 + 9728) + 1024;
__global__ void __launch_bounds__(512) side_kernel(const __grid_constant__ CUtensorMap tmK, const __grid_constant__ CUtensorMap tmV,
                                                   const __nv_bfloat16* __restrict__ shp, const __nv_bfloat16* __restrict__ hp,
                                                   const __nv_bfloat16* __restrict__ Dp, int mode, int unit0, int ch_base, int utarget) {
  extern __shared__ __align__(1024) uint8_t smraw[];
  const uint32_t sb = s2u(smraw);
  const uint32_t bar = sb + SMEM_SIDE - 1024;
  const int tid = threadIdx.x, lane = tid & 31, warp = uni(tid >> 5);
  const uint32_t t0 = clk32();
  if (mode & 1) {
    const int u = unit0 + blockIdx.x;
    if (tid == 0) {
      mbar_init(bar, 1);
      fence_async_smem();
      mbar_expect(bar, 2 * KVIN);
      kv_load(sb, &tmK, &tmV, shp, (u >> 3) * 32, (u & 7) * 2, bar);
      kv_load(sb + 18432, &tmK, &tmV, shp, (u >> 3) * 32, (u & 7) * 2 + 1, bar);
    }
    __syncthreads();
    if (warp < 8) {
      mbar_wait(bar, 0, t0);
      KvRegs o;
      KvAddr ad;
      kv_addr(ad, lane);
      kv_compute(o, ad, sb + (warp >> 2) * 18432, warp & 3);
      kv_store(o, (u >> 3) * 32 + (warp & 3) * 8, (u & 7) * 2 + (warp >> 2), lane);
      asm volatile("fence.acq_rel.gpu;" ::: "memory");
    }
    __syncthreads();
    if (warp == 0) kv_publish(lane);
  }
  if (!(mode & 2)) return;
  const int wg = warp >> 2, ch = ch_base + blockIdx.x * 4 + wg;
  const uint32_t hs = sb + wg * (18432 + 9728), us = hs + 18432;
  HRegs<128> hr;
  conv_load_h(hr, hp + (size_t)ch * 2048, Dp + ch, tid & 127);
  conv_expand_h(hr, hs, tid & 127);
  flag_wait(&g_ucnt, utarget, t0);
  URegs ur;
  conv_load_u(ur, g_U + (size_t)ch * 2048, tid & 127);
  conv_build_u(ur, us, tid & 127);
  fence_async_smem();
  bar_sync(1 + wg, 128);
  conv_channel(hs, us, hs, 1 + wg, warp & 3, lane, 0u);
  fence_async_smem();
  bar_sync(1 + wg, 128);
  if ((tid & 127) == 0) {
    bulk_store(g_Y + (size_t)ch * 2048, hs, 4096);
    bulk_commit();
    bulk_wait0();
    asm volatile("red.relaxed.gpu.global.add.u32 [%0],%1;" ::"l"(&g_ycnt[ch >> 6]), "r"(1u) : "memory");
  }
}

struct Ctx {
  uint32_t sb;
  uint32_t t0;
};
DEVI uint32_t barx(const Ctx& c, int i) { return c.sb + OFF_BAR + 8 * i; }
DEVI uint32_t xslot(const Ctx& c, int p) { return c.sb + OFF_X + p * XSLOT; }
DEVI void bwait(const Ctx& c, int i, uint32_t ph) { mbar_wait(barx(c, i), ph, c.t0); }
DEVI void bwait_cl(const Ctx& c, int i, uint32_t ph) { mbar_wait_cl(barx(c, i), ph, c.t0); }
DEVI void cluster_wait() { asm volatile("barrier.cluster.wait.aligned;" ::: "memory"); }

DEVI int ord(int rank, int i) { return i == 0 ? rank : (i <= rank ? i - 1 : i); }

DEVI void row_stats_mma(float* d, uint32_t a1, uint32_t a2) {
  uint32_t f[8];
  ldsm4(f, a1);
  ldsm4(f + 4, a2);
  const uint32_t ones = 0x3f803f80u;
  mma16816_z(d, f[0], ones, f[1], ones, f[0], f[1]);
  mma16816_z(d + 4, f[4], ones, f[5], ones, f[4], f[5]);
  mma16816(d, f[2], ones, f[3], ones, f[2], f[3]);
  mma16816(d + 4, f[6], ones, f[7], ones, f[6], f[7]);
}
DEVI float2 row_stats_fin(const float* d, int lane) {
  const bool odd = lane & 4;
  const int src = (lane & 28) | (lane >> 3);
  const float s = __shfl_sync(~0u, odd ? d[3] + d[7] : d[2] + d[6], src);
  const float q = __shfl_sync(~0u, odd ? d[1] + d[5] : d[0] + d[4], src);
  return make_float2(s, q);
}
DEVI void stats_send(float2 v, uint32_t dst, uint32_t bar, int lane) {
  st_async2(mapa(dst, lane & 3), v.x, v.y, mapa(bar, lane & 3));
  st_async2(mapa(dst, (lane & 3) + 4), v.x, v.y, mapa(bar, (lane & 3) + 4));
}
DEVI float2 finish_stats(uint32_t a, int pitch) {
  float2 v[8];
#pragma unroll
  for (int p = 0; p < 8; p++) v[p] = lds64f(a + p * pitch);
  const float s = ((v[0].x + v[1].x) + (v[2].x + v[3].x)) + ((v[4].x + v[5].x) + (v[6].x + v[7].x));
  const float q = ((v[0].y + v[1].y) + (v[2].y + v[3].y)) + ((v[4].y + v[5].y) + (v[6].y + v[7].y));
  const float mean = s * (1.f / 512.f);
  const float var = fmaxf(q * (1.f / 512.f) - mean * mean, 0.f);
  float r;
  asm("rsqrt.approx.ftz.f32 %0,%1;" : "=f"(r) : "f"(var + 1e-5f));
  return make_float2(r, -mean);
}

#define ST(i) do { if (w == 0) STAMP(wg * 20 + layer * 10 + (i)); } while (0)

__global__ void __cluster_dims__(8, 1, 1) __launch_bounds__(512, 1)
main_kernel(const __grid_constant__ CUtensorMap tmX72, const __grid_constant__ CUtensorMap tmX7,
            const __grid_constant__ CUtensorMap tmW, const __grid_constant__ CUtensorMap tmWo,
            const __grid_constant__ CUtensorMap tmY, const __grid_constant__ CUtensorMap tmK,
            const __grid_constant__ CUtensorMap tmV, __nv_bfloat16* __restrict__ outp,
            const __nv_bfloat16* __restrict__ wqkvp, const __nv_bfloat16* __restrict__ wop,
            const __nv_bfloat16* __restrict__ kp, const __nv_bfloat16* __restrict__ vp,
            const __nv_bfloat16* __restrict__ shp, const __nv_bfloat16* __restrict__ hp,
            const __nv_bfloat16* __restrict__ Dp, int do_conv) {
  extern __shared__ __align__(1024) uint8_t smraw[];
  Ctx c;
  c.sb = s2u(smraw);
  c.t0 = clk32();
  asm volatile("griddepcontrol.launch_dependents;" ::: "memory");
  const int lane = threadIdx.x & 31;
  const int warp = uni(threadIdx.x >> 5);
  const int w = warp & 3, wg = warp >> 2;
  const int rank = blockIdx.x & 7, tile = blockIdx.x >> 3;
  const int ciA = 136 * tile;

  const int ciB = ciA + 72, ciH = ciA - 8;
  const int xH = (ciH >= 1024 ? 512 : 0) + rank * 64, yH = (ciH >= 1024 ? ciH - 1024 : ciH) + 1;
  const int xA = (ciA >> 10) * 512 + rank * 64, yA = ciA & 1023;
  const int xB = (ciB >> 10) * 512 + rank * 64, yB = ciB & 1023;
  const uint32_t own = xslot(c, rank);
  if (elect()) {
    const int cnt = warp < 12 ? 1 : (warp == 12 ? 8 : 12);
#pragma unroll
    for (int i = 0; i < 7; i++) mbar_init(barx(c, warp * 7 + i), cnt);
    asm volatile("fence.mbarrier_init.release.cluster;" ::: "memory");
    fence_async_smem();
    if (warp == 5) {
      const uint32_t xb = barx(c, B_XOWN);
      tma2d(own, &tmX72, xA, yA, xb);
      tma2d(own + 9216, &tmX72, xB, yB, xb);
      tma2d(own + 145 * 128, &tmX7, xH, yH, xb);
      STAMP(73);
    }
    if (warp == 0) {
#pragma unroll
      for (int s = 0; s < NRING; s++)
        tma2d(c.sb + OFF_RING + s * RSLOT, &tmW, ((s % 3) == 0 ? 512 : ((s % 3) == 1 ? 0 : 1024)) + rank * 64, ord(rank, s / 3) * 64,
              barx(c, B_FULL + s));
    }
  }
  if (warp == 1 || warp == 2) {
    const uint32_t o = 0x3f803f80u;
    const int i = threadIdx.x - 32;
    sts128(xslot(c, i >> 3) + 144 * 128 + (i & 7) * 16, o, o, o, o);
    fence_async_smem();
  }
  __syncwarp();
  asm volatile("barrier.cluster.arrive.relaxed.aligned;" ::: "memory");
  __syncthreads();
  if (warp == 0) STAMP(71);

  const int ch0 = tile * 32 + rank * 4;

  if (warp >= 12) {
    asm volatile("setmaxnreg.dec.sync.aligned.u32 80;");
    {
      const int b = threadIdx.x - 384;
      if (b < B_MRQ) {
        uint32_t n = 8192;
        if (b >= 32 && b < 35) n = 9216;
        if (b == B_XOWN || b >= B_XFULL) n = 151 * 128;
        if (b == B_KIN || b == B_VIN) n = KVIN;
        if (b == B_URAW) n = 16384;
        if (b == B_STQ) n = 7 * 1216;
        if (b == B_STB) n = 8 * 1152;
        mbar_expect(barx(c, b), n);
      }
    }
    cluster_wait();
    if (warp == 12) {
      const bool el = elect();
      uint32_t ph = 0, slot = 0, fb = barx(c, B_FULL + NRING);
#define ISSUE(TM, X, Y, FB)                                                        \
      {                                                                            \
        bwait(c, B_EMPTY + slot, ph);                                              \
        if (el) tma2d(c.sb + OFF_RING + slot * RSLOT, TM, X, Y, FB);               \
        fb += 8;                                                                   \
        if (++slot == NRING) { slot = 0; ph ^= 1; }                                \
      }
#pragma unroll 1
      for (int layer = 0; layer < 2; layer++) {
#pragma unroll 1
        for (int i = layer ? 0 : 2; i < 4; i++) {
          const int y = ord(rank, i) * 64;
#pragma unroll 1
          for (int part = 0; part < 3; part++) ISSUE(&tmW, ((0x201 >> (4 * part)) & 3) * 512 + rank * 64, y, fb)
        }
#pragma unroll 1
        for (int part = 0; part < 3; part++) {
          const int x = ((0x201 >> (4 * part)) & 3) * 512 + rank * 64;
#pragma unroll 1
          for (int p = ord(rank, 4); p < 8; p += (p + 1 == rank ? 2 : 1)) ISSUE(&tmW, x, p * 64, fb)
        }
        const uint32_t seq = layer ? 0x76543210u : OSEQ1;
#pragma unroll 1
        for (int i = 0; i < 8; i++) ISSUE(&tmWo, rank * 64, ord(rank, (seq >> (4 * i)) & 7) * 64, fb)
        if (layer == 0) {
          flag_wait(&g_ycnt[rank], 64u, c.t0);
          STAMP(60);
#pragma unroll 1
          for (int i = 0; i < 4; i++) ISSUE(&tmY, ciA + (i >> 1) * 72, rank * 64 + (i & 1) * 32, barx(c, B_FULL + 32 + (i >> 1)))
        }
      }
      if (el && atomicAdd(&g_done, 1u) == gridDim.x - 1) {
        for (int i = 0; i < 8; i++) g_ycnt[i] = 0;
        g_ucnt = 0;
        g_done = 0;
      }
    } else if (warp == 13) {
      const int pp = ord(rank, lane & 7);
      const uint32_t xfb = barx(c, B_XFULL + pp);
      const uint16_t others = (uint16_t)(0xff ^ (1u << rank));
      if (lane == 0) {
        tma2d_mc(own, &tmX72, xA, yA, xfb, others);
        tma2d_mc(own + 9216, &tmX72, xB, yB, xfb, others);
        tma2d_mc(own + 145 * 128, &tmX7, xH, yH, xfb, others);
      }
#pragma unroll 1
      for (int ex = 0; ex < 3; ex++) {
        if (ex != 1) {
          bar_sync(6, 416);
          if (lane >= 1 && lane < 8) {
            const uint32_t a = c.sb + OFF_STQ + rank * 1216;
            bulk_s2s(mapa(a, pp), a, 1216, mapa(barx(c, B_STQ), pp));
          }
          bwait(c, B_STQ, ex >> 1);
          if (lane == 0 && ex == 0) mbar_expect(barx(c, B_STQ), 7 * 1216);
#pragma unroll 1
          for (int r = lane; r < 152; r += 32) {
            const float2 v = finish_stats(c.sb + OFF_STQ + r * 8, 1216);
            sts64f(c.sb + OFF_STQ + (rank == 0) * 1216 + r * 8, v.x, v.y);
          }
          __syncwarp();
          if (lane == 0) mbar_arrive(barx(c, B_MRQ));
          if (ex == 0 && do_conv) {
#pragma unroll
            for (int i = 0; i < 4; i++) asm volatile("prefetch.global.L2 [%0];" ::"l"(hp + (size_t)(ch0 + i) * 2048 + lane * 64));
            if (lane == 0) asm volatile("prefetch.global.L2 [%0];" ::"l"(Dp + ch0));
          }
        }
        uint8_t* gb = (ex == 1 ? g_exX : g_exO) + (size_t)tile * 8 * XSLOT + 256;
        if (ex != 1) {
          bwait(c, B_ATTLD, ex >> 1);
          if (lane >= 1 && lane < 8) mbar_expect(xfb, XSLOT - 256);
          __syncwarp();
          if (ex == 2 && lane < 8) mbar_arrive_remote(mapa(barx(c, B_XFREE), lane));
        }
        bwait(c, B_STAGED, ex & 1);
        STAMP(62 + ex * 3);
        if (lane == 0) {
          const uint32_t ts = clk32();
          bulk_store(gb + rank * XSLOT, own + 256, XSLOT - 256);
          bulk_commit();
          if (ex == 2) bwait(c, B_XFREE, 0);
          bulk_wait0();
          STAMP(63 + ex * 3);
          if (ex > 0) {
            while (clk32() - ts < 560u + rank * STAG) {}
            bulk_load_mc(own + 256, gb + rank * XSLOT, XSLOT - 256, xfb, others);
          }
          STAMP(64 + ex * 3);
        }
        if (ex == 0) {
          __syncwarp();
          if (do_conv) bwait(c, B_TAB + 3, 0);
          if (lane < 8) mbar_arrive_remote(mapa(barx(c, B_OSTORED), lane));
          bwait(c, B_OSTORED, 0);
          const int step = do_conv ? (0x30214420u >> (4 * (lane & 7))) & 7 : 0;
#pragma unroll 1
          for (int st = 0; st < (do_conv ? 5 : 1); st++) {
            if (st > 0) {
              bwait(c, B_YST + st - 1, 0);
              if (st == 4) STAMP(74);
              if (lane == 0) {
                bulk_store(g_Y + (size_t)(ch0 + st - 1) * 2048, xslot(c, ord(rank, (HSLOT >> (4 * st - 4)) & 7)), 4096);
                bulk_commit();
                bulk_wait0_read();
              }
              __syncwarp();
            }
            if (lane >= 1 && lane < 8 && step == st) bulk_load(xslot(c, pp) + 256, gb + pp * XSLOT, XSLOT - 256, xfb);
          }
          if (do_conv && lane == 0) {
            bulk_wait0();
            asm volatile("red.relaxed.gpu.global.add.u32 [%0],%1;" ::"l"(&g_ycnt[ch0 >> 6]), "r"(4u) : "memory");
            STAMP(61);
          }
          if (lane >= 1 && lane < 8) {
            mbar_wait(xfb, 1, c.t0);
            mbar_expect(xfb, XSLOT - 256);
          }
          __syncwarp();
        }
      }
    } else {
      const int at = threadIdx.x - 448;
      const uint32_t vb = xslot(c, ord(rank, 1));
      {
        const uint8_t* pw = (const uint8_t*)wqkvp + min(blockIdx.x * 104u + at, 12287u - 64u) * 128u;
        asm volatile("prefetch.global.L2 [%0];" ::"l"(pw));
        if (at < 40) asm volatile("prefetch.global.L2 [%0];" ::"l"(pw + 64 * 128));
      }
      bwait(c, B_XOWN, 0);
      if (blockIdx.x < 64) asm volatile("prefetch.global.L2 [%0];" ::"l"((const uint8_t*)wop + blockIdx.x * 8192 + at * 128));
      if (do_conv) {
#pragma unroll
        for (int i = 0; i < 2; i++) {
          const size_t o = (size_t)(rank * 256 + (tile & 1) * 128 + i * 64 + at) * 512 + (tile >> 1) * 64;
          asm volatile("prefetch.global.L2 [%0];" ::"l"(kp + o));
          asm volatile("prefetch.global.L2 [%0];" ::"l"(vp + o));
        }
        KvAddr ad;
        kv_addr(ad, lane);
        if (at == 32) {
          bwait(c, B_TD, 0);
          kv_load(own, &tmK, &tmV, shp, tile * 32, rank * 2, barx(c, B_KIN));
        }
#pragma unroll 1
        for (int it = 0; it < 4; it++) {
          const int col = 2 * (it & 1) + (warp & 1);
          if (it == 1 && at == 32) {
            bwait(c, B_TD + 1, 0);
            kv_load(vb, &tmK, &tmV, shp, tile * 32, rank * 2 + 1, barx(c, B_VIN));
          }
          __syncwarp();
          bwait(c, B_KIN + (it >> 1), 0);
          if (warp == 14) STAMP(148 + it);
          KvRegs o;
          kv_compute(o, ad, it < 2 ? own : vb, col);
          if (warp == 14) STAMP(152 + it);
          const int dst = 2 * col + (lane & 1);
          const uint32_t da = mapa(c.sb + OFF_URAW + (255 - (rank * 2 + (it >> 1)) * 16 - (lane >> 1)) * 16, dst), db = mapa(barx(c, B_URAW), dst);
#pragma unroll
          for (int ch = 0; ch < 4; ch++) {
            const uint4 v = kv_pack(o, ch);
            st_async4(da + ch * 4096, v.x, v.y, v.z, v.w, db);
          }
        }
        if (lane == 0) mbar_arrive_n(barx(c, B_KFREE), 4);
        bar_sync(5, 64);
        bwait_cl(c, B_URAW, 0);
        if (warp == 14) STAMP(76);
#pragma unroll 1
        for (int ch = 0; ch < 4; ch++) {
          URegs ur[2];
          const int a2 = pin(at);
          conv_load_u_smem(ur[0], c.sb + OFF_URAW + ch * 4096, a2);
          conv_load_u_smem(ur[1], c.sb + OFF_URAW + ch * 4096, a2 + 64);
          if (ch == 2) bwait(c, B_ATTLD, 0);
          const uint32_t us = xslot(c, ord(rank, 1 + (ch >> 1))) + (ch & 1) * UCH;
          conv_build_u(ur[0], us, a2);
          conv_build_u(ur[1], us, a2 + 64);
          fence_async_smem();
          __syncwarp();
          if (lane == 0) mbar_arrive_n(barx(c, B_TAB + ch), 2);
          if (ch == 1 && warp == 14) STAMP(75);
        }
        HRegs<64> hr;
        conv_load_h(hr, hp + (size_t)(ch0 + 3) * 2048, Dp + ch0 + 3, at);
        conv_expand_h(hr, xslot(c, ord(rank, 3)), at);
        fence_async_smem();
        __syncwarp();
        if (lane == 0) mbar_arrive_n(barx(c, B_TAB + 3), 4);
      }
    }
  } else {
    asm volatile("setmaxnreg.inc.sync.aligned.u32 144;");
    const int tid = w * 32 + lane;
    const int g = lane >> 2, t = lane & 3, mi = lane >> 3, r8 = lane & 7;
    const bool l0 = lane == 0;
    const uint32_t hoff = pin(w * SUBT + lane * 16);
    const uint32_t alo = (((c.sb & 0x3FFFF) + OFF_RING) >> 4) | (64u << 16);
    const uint32_t rsa = pin(own + 256 + (mi >> 1) * SUBT + (mi & 1) * 128 + r8 * 16 + warp * 256);
    uint32_t xr[10][2], yf[10][2];
    float cs0 = 0.f, cs1 = 0.f;
    uint32_t sa1 = pin(own + (warp * 8 + r8) * 128 + ((mi ^ r8) << 4)), sa2 = pin(sa1 ^ 64), sgs = warp < 7 ? 12 * 1024 : 0;
    const uint32_t xlo = (c.sb & 0x3FFFF) >> 4;

#pragma unroll 1
    for (int layer = 0; layer < 2; layer++) {
      const int sb0 = layer * 36;
      {
        float acc[76];
        float sd[16];
        bwait(c, layer ? B_STAGED : B_XOWN, layer);
        if (warp == 8 && layer == 0) STAMP(72);
        row_stats_mma(sd, sa1, sa2);
        row_stats_mma(sd + 8, sa1 + sgs, sa2 + sgs);
        {
          const bool odd = lane & 4;
          const uint32_t dst = c.sb + OFF_STQ + rank * 1216 + warp * 64 + g * 8;
          if ((g >> 1) == t) {
            sts64f(dst, odd ? sd[3] + sd[7] : sd[2] + sd[6], odd ? sd[1] + sd[5] : sd[0] + sd[4]);
            if (warp < 7) sts64f(dst + 768, odd ? sd[11] + sd[15] : sd[10] + sd[14], odd ? sd[9] + sd[13] : sd[8] + sd[12]);
          }
          fence_async_smem();
          bar_arrive(6, 416);
        }
        bwait(c, B_FULL + sb0 + wg, 0);
        bar_sync(4, 384);
        ST(0);
#define QKV_GEMM(WG0, WG, BLO, BHI, BSTEP)                                                                     \
        {                                                                                                      \
          uint32_t da = alo + wg * (RSLOT >> 4), db = xlo + (BLO) + rank * (XSLOT >> 4);                       \
          wg_fence();                                                                                          \
          WG0(acc, desc64(da, 0x40000040u), desc64(db, BHI), 0);                                               \
          _Pragma("unroll 1")                                                                                  \
          for (int i = 0; i < 4; i++) {                                                                        \
            if (i > 0) {                                                                                       \
              const int p = ord(rank, i);                                                                      \
              da = alo + (3 * (i & 1) + wg) * (RSLOT >> 4);                                                    \
              db = xlo + (BLO) + p * (XSLOT >> 4);                                                             \
              bwait(c, B_XFULL + p, 0);                                                                        \
              bwait(c, B_FULL + sb0 + 3 * i + wg, 0);                                                          \
              if (w == 0) STAMP(80 + sb0 + 3 * i + wg);                                                        \
              wg_fence();                                                                                      \
              WG(acc, desc64(da, 0x40000040u), desc64(db, BHI), 1);                                            \
              wg_commit();                                                                                     \
              wg_wait<1>();                                                                                    \
              if (l0 && i > 1) { mbar_arrive_n(barx(c, B_EMPTY + 3 * (~i & 1) + wg), 3); mbar_arrive(barx(c, B_TD + i - 1)); } \
            }                                                                                                  \
            wg_fence();                                                                                        \
            WG(acc, desc64(da + 128, 0x40000040u), desc64(db + BSTEP, BHI), 1);                                \
            WG(acc, desc64(da + 256, 0x40000040u), desc64(db + 2 * BSTEP, BHI), 1);                            \
            WG(acc, desc64(da + 384, 0x40000040u), desc64(db + 3 * BSTEP, BHI), 1);                            \
            wg_commit();                                                                                       \
            if (i == 0) {                                                                                      \
              if (layer == 0) {                                                                                \
                if (wg < 2) {                                                                                  \
                  const uint32_t a = own + (72 * wg + (mi >> 1) * 8 + r8) * 128 + (((2 * w + (mi & 1)) ^ r8) << 4); \
                  _Pragma("unroll")                                                                            \
                  for (int j = 0; j < 8; j += 2) ldsm4t(&xr[j][0], a + j * 1024);                              \
                  ldsm2t(&xr[8][0], a + 8192);                                                                 \
                }                                                                                              \
              }                                                                                                \
              wg_wait<0>();                                                                                    \
              if (l0) { mbar_arrive_n(barx(c, B_EMPTY + wg), 3); mbar_arrive(barx(c, B_TD)); }                 \
            }                                                                                                  \
          }                                                                                                    \
                                                                        \
          uint32_t eb = barx(c, B_EMPTY + 3 + wg), td = barx(c, B_TD + 3);                                        \
          if (wg > 0) {                                                                                        \
            wg_wait<0>();                                                                                      \
            if (l0) { mbar_arrive_n(eb, 3); mbar_arrive(td); }                                                 \
            eb = 0; td = 0;                                                                                    \
            bar_sync(9 + wg, 256);                                                                             \
          } else {                                                                                             \
            for (int i = 4; i < 8; i++) bwait(c, B_XFULL + ord(rank, i), 0);                                   \
          }                                                                                                    \
          int slot = (0x240 >> (4 * wg)) & 7, p = ord(rank, 4);                                                                \
          uint32_t fb = barx(c, B_FULL + sb0 + 12 + 4 * wg);                                                    \
          mbar_wait(fb, 0, c.t0);                                                                              \
          _Pragma("unroll 1")                                                                                  \
          for (int i = 0; i < 4; i++) {                                                                        \
            da = alo + slot * (RSLOT >> 4);                                                                    \
            db = xlo + (BLO) + p * (XSLOT >> 4);                                                               \
            if (w == 0) STAMP(80 + sb0 + 12 + 4 * wg + i);                                                      \
            wg_fence();                                                                                        \
            WG(acc, desc64(da, 0x40000040u), desc64(db, BHI), 1);                                              \
            WG(acc, desc64(da + 128, 0x40000040u), desc64(db + BSTEP, BHI), 1);                                \
            wg_commit();                                                                                       \
            fb += 8;                                                                                           \
            const bool ok = mbar_test(fb, 0);                                                                  \
            wg_wait<1>();                                                                                      \
            if (l0 && eb) mbar_arrive_n(eb, 3);                                                                \
            if (l0 && td) mbar_arrive(td);                                                                     \
            WG(acc, desc64(da + 256, 0x40000040u), desc64(db + 2 * BSTEP, BHI), 1);                            \
            eb = barx(c, B_EMPTY + slot);                                                                      \
            td = i == 1 ? barx(c, B_HFREE) : 0;                                                                \
            slot = slot == 5 ? 0 : slot + 1;                                                                   \
            p += p + 1 == rank ? 2 : 1;                                                                        \
            if (i == 2 && wg < 2) bar_arrive(10 + wg, 256);                                                    \
            WG(acc, desc64(da + 384, 0x40000040u), desc64(db + 3 * BSTEP, BHI), 1);                            \
            wg_commit();                                                                                       \
            if (!ok && i < 3) mbar_wait(fb, 0, c.t0);                                                          \
          }                                                                                                    \
          wg_wait<0>();                                                                                        \
          if (l0) {                                                                                            \
            mbar_arrive_n(eb, 3);                                                                              \
            if (wg < 2) mbar_arrive(barx(c, B_KQDONE));                                                        \
          }                                                                                                    \
        }
        if (layer == 0) {
          QKV_GEMM(wg0_n152, wg_n152, (1u << 16), 0x40000040u, 2)
        } else {
          acc[72] = acc[73] = acc[74] = acc[75] = 0.f;
          QKV_GEMM(wg0_n144, wg_n144, (16u | (8u << 16)), 16u, (SUBT >> 4))
        }
        fence_regs<76>(acc);
        if (layer == 0) cluster_wait();
        sa1 = rsa; sa2 = rsa + 2 * SUBT; sgs = warp < 7 ? 12 * 256 : 0;
        ST(1);
        if (layer == 0) {
          cs0 = __shfl_sync(~0u, acc[72], lane & ~3);
          cs1 = __shfl_sync(~0u, acc[74], lane & ~3);
        }
        bwait(c, B_MRQ, layer);
        bwait(c, wg == 2 ? B_KQDONE : B_TD + 3, layer);
        const uint32_t mr = c.sb + OFF_STQ + (rank == 0) * 1216 + t * 16;
        const uint32_t sa = xslot(c, ord(rank, (0x632 >> (4 * wg)) & 7)) + hoff;
        float4 mq[6];
#pragma unroll
        for (int j = 0; j < 4; j++) mq[j] = lds128f(mr + j * 64);
#pragma unroll
        for (int j = 0; j < 18; j += 2) {
          if (j + 4 < 19) mq[(j + 4) % 6] = lds128f(mr + (j + 4) * 64);
          if (j + 5 < 19) mq[(j + 5) % 6] = lds128f(mr + (j + 5) * 64);
          const float4 m = mq[j % 6], n = mq[(j + 1) % 6];
          const float* a = &acc[j * 4];
          stsm4t(sa + 256 + j * 256,
                 pack2(fmaf(m.y, cs0, a[0]) * m.x, fmaf(m.w, cs0, a[1]) * m.z), pack2(fmaf(m.y, cs1, a[2]) * m.x, fmaf(m.w, cs1, a[3]) * m.z),
                 pack2(fmaf(n.y, cs0, a[4]) * n.x, fmaf(n.w, cs0, a[5]) * n.z), pack2(fmaf(n.y, cs1, a[6]) * n.x, fmaf(n.w, cs1, a[7]) * n.z));
        }
        {
          const float4 m = mq[0];
          stsm2t(sa, pack2(fmaf(m.y, cs0, acc[72]) * m.x, fmaf(m.w, cs0, acc[73]) * m.z),
                 pack2(fmaf(m.y, cs1, acc[74]) * m.x, fmaf(m.w, cs1, acc[75]) * m.z));
        }
      }
      const bool cv = layer == 0 && do_conv;
      const bool hact = cv && wg < 2;
#pragma unroll 1
      for (int ph = (cv && wg == 0) ? 0 : 1; ph < 2; ph++) {
      const int hch = ph ? 2 - wg : 0;
      HRegs<128> hr;
      conv_load_h(hr, hp + (size_t)(ch0 + hch) * 2048, Dp + ch0 + hch, tid, hact);
      if (ph) {
      ST(2);
      bar_sync(4, 384);
      {
        uint32_t kf[8][2], vf[8][2], qf[3][4];
        const uint32_t ka = xslot(c, ord(rank, 2)) + hoff + wg * 1536, va = xslot(c, ord(rank, 6)) + hoff + wg * 1536;
        const uint32_t sta = own + hoff + 256 + wg * 1536;
        const uint32_t qa = xslot(c, ord(rank, 3)) + hoff + 256 + wg * 1536 + (mi == 1 ? 128 : (mi == 2 ? -128 : 0));
#pragma unroll
        for (int u = 0; u < 3; u++) { ldsm4(qf[u], qa + u * 512); ldsm4(&kf[2 * u][0], ka + u * 512); }
        ldsm2(&kf[6][0], ka + 1536);
#pragma unroll
        for (int u = 0; u < 3; u++) ldsm4t(&vf[2 * u][0], va + u * 512);
        ldsm2t(&vf[6][0], va + 1536);
        __syncwarp();
        if (l0) mbar_arrive(barx(c, B_ATTLD));
        const bool prev0 = 2 * t > g, prev1 = 2 * t + 1 > g;
        const uint32_t mprev = (prev0 ? 0xffffu : 0u) | (prev1 ? 0xffff0000u : 0u);
        float l[6][2], mx[6];
#pragma unroll
        for (int u = 0; u < 3; u++) {
          float s0[4], s1[4], s2[4];
          mma16816_z(s0, qf[u][0], qf[u][1], qf[u][2], qf[u][3], kf[2 * u][0], kf[2 * u][1]);
          mma16816_z(s1, qf[u][0], qf[u][1], qf[u][2], qf[u][3], kf[2 * u + 1][0], kf[2 * u + 1][1]);
          mma16816_z(s2, qf[u][0], qf[u][1], qf[u][2], qf[u][3], kf[2 * u + 2][0], kf[2 * u + 2][1]);
          if (u == 0 && wg == 0 && (layer == 1 || tile == 0)) { s0[0] = -INFINITY; s0[1] = -INFINITY; }
          if (u == 1 && wg == 1 && tile == 7) { s1[2] = -INFINITY; s1[3] = -INFINITY; }
          l[2 * u][0] = prev0 ? s0[0] : s1[0];
          l[2 * u][1] = prev1 ? s0[1] : s1[1];
          l[2 * u + 1][0] = prev0 ? s1[2] : s2[2];
          l[2 * u + 1][1] = prev1 ? s1[3] : s2[3];
        }
        const float sc2 = 0.25f * 1.4426950408889634f;
#pragma unroll
        for (int j = 0; j < 6; j++) mx[j] = fmaxf(l[j][0], l[j][1]);
#pragma unroll
        for (int j = 0; j < 6; j++) mx[j] = fmaxf(mx[j], __shfl_xor_sync(~0u, mx[j], 1));
#pragma unroll
        for (int j = 0; j < 6; j++) mx[j] = -sc2 * fmaxf(mx[j], __shfl_xor_sync(~0u, mx[j], 2));
        const uint32_t ones = 0x3f803f80u;
        if (do_conv) bwait(c, B_KFREE, 0);
#pragma unroll
        for (int u = 0; u < 3; u++) {
          uint32_t o[4];
#pragma unroll
          for (int h = 0; h < 2; h++) {
            const int j = 2 * u + h;
            const uint32_t p = pack2(ex2(fmaf(l[j][0], sc2, mx[j])), ex2(fmaf(l[j][1], sc2, mx[j])));
            float d[4], sm[4];
            mma16816_z(d, vf[j][0], vf[j][1], vf[j + 1][0], vf[j + 1][1], p & mprev, p & ~mprev);
            asm volatile("mma.sync.aligned.m16n8k8.row.col.f32.bf16.bf16.f32 {%0,%1,%2,%3},{%4,%4},{%5},{%6,%6,%6,%6};"
                         : "=f"(sm[0]), "=f"(sm[1]), "=f"(sm[2]), "=f"(sm[3]) : "r"(ones), "r"(p), "f"(0.f));
            const float r0 = rcp(sm[0]), r1 = rcp(sm[1]);
            o[2 * h] = pack2(d[0] * r0, d[1] * r1);
            o[2 * h + 1] = pack2(d[2] * r0, d[3] * r1);
          }
          stsm4t(sta + u * 512, o[0], o[1], o[2], o[3]);
        }
        fence_async_smem();
        __syncwarp();
        if (l0) mbar_arrive(barx(c, B_STAGED));
      }
      ST(4);
      }
      if (hact) {
        bwait(c, B_HFREE, 0);
        conv_expand_h(hr, xslot(c, ord(rank, (HSLOT >> (4 * hch)) & 7)), tid);
        fence_async_smem();
        __syncwarp();
        if (l0) mbar_arrive_n(barx(c, B_TAB + hch), 2);
      }
      }
      if (cv) {
        bwait(c, B_STAGED, 0);
#pragma unroll 1
        for (int ch = 2 - wg; ch < 4; ch += 3) {
          const uint32_t hs = xslot(c, ord(rank, (HSLOT >> (4 * ch)) & 7)), us = xslot(c, ord(rank, 1 + (ch >> 1))) + (ch & 1) * UCH;
          bwait(c, B_TAB + ch, 0);
          if (ch >= 2) bwait(c, B_CVD + ch - 2, 0);
          if (ch < 3) ST(3);
          conv_channel(hs, us, hs, 1 + wg, w, lane, ch == 2 ? 0u : barx(c, B_CVD + (ch >> 1) + (ch & 1)));
          fence_async_smem();
          __syncwarp();
          if (l0) mbar_arrive_n(barx(c, B_YST + ch), 3);
        }
        bwait(c, B_CVD + 2, 0);
      }
      ST(5);
      {
        float acc[36];
        const uint32_t sta = own + hoff + 256 + wg * 2304;
#pragma unroll
        for (int j = 0; j < 9; j++) {
          acc[j * 4 + 0] = bflo(xr[j][0]); acc[j * 4 + 1] = bfhi(xr[j][0]);
          acc[j * 4 + 2] = bflo(xr[j][1]); acc[j * 4 + 3] = bfhi(xr[j][1]);
        }
        fence_regs<36>(acc);
        if (wg < 2) {
          bwait(c, B_STAGED, 0);
          const uint32_t blo = (((c.sb & 0x3FFFF) + 256 + wg * 2304) >> 4) | (8u << 16);
          const uint32_t seq = layer ? 0x76543210u : OSEQ1;
          uint32_t da = alo, db = blo + rank * (XSLOT >> 4);
          bwait(c, B_FULL + sb0 + 24, 0);
#pragma unroll 1
          for (int i = 0; i < 8; i++) {
            const int pn = ord(rank, (seq >> (4 * i + 4)) & 7);
            if (warp == 0) STAMP(80 + sb0 + 24 + i);
            wg_fence();
            wg_n72(acc, desc64(da, 0x40000040u), desc64(db, 16u), 1);
            wg_n72(acc, desc64(da + 128, 0x40000040u), desc64(db + (SUBT >> 4), 16u), 1);
            const bool ok = mbar_test(barx(c, B_XFULL + pn), 1) & mbar_test(barx(c, B_FULL + sb0 + 25 + i), 0);
            wg_commit();
            wg_wait<1>();
            if (l0 && i > 0) mbar_arrive_n(barx(c, B_EMPTY + (i < 7 ? i - 1 : 0)), 1 + (w & 1));
            wg_n72(acc, desc64(da + 256, 0x40000040u), desc64(db + 2 * (SUBT >> 4), 16u), 1);
            wg_n72(acc, desc64(da + 384, 0x40000040u), desc64(db + 3 * (SUBT >> 4), 16u), 1);
            wg_commit();
            if (i == 7) break;
            da = alo + (i < 5 ? i + 1 : i - 5) * (RSLOT >> 4);
            db = blo + pn * (XSLOT >> 4);
            if (!__all_sync(~0u, ok)) {
              bwait(c, B_XFULL + pn, 1);
              bwait(c, B_FULL + sb0 + 25 + i, 0);
            }
          }
          wg_wait<0>();
          fence_regs<36>(acc);
          if (l0) mbar_arrive_n(barx(c, B_EMPTY + 1), 1 + (w & 1));
          ST(6);
#pragma unroll
          for (int j = 0; j < 8; j += 2)
            stsm4t(sta + j * 256, pack2(acc[j * 4], acc[j * 4 + 1]), pack2(acc[j * 4 + 2], acc[j * 4 + 3]),
                   pack2(acc[j * 4 + 4], acc[j * 4 + 5]), pack2(acc[j * 4 + 6], acc[j * 4 + 7]));
          stsm2t(sta + 2048, pack2(acc[32], acc[33]), pack2(acc[34], acc[35]));
        } else {
          for (int i = 1; i < 8; i++) bwait(c, B_XFULL + ord(rank, i), 1);
        }
        bar_sync(4, 384);
        {
          const uint32_t dst = c.sb + OFF_STB + rank * 1152 + warp * 64 + g * 8;
          float sd[16];
          row_stats_mma(sd, rsa, rsa + 2 * SUBT);
          row_stats_mma(sd + 8, rsa + 6 * 256, rsa + 2 * SUBT + 6 * 256);
          const float2 v0 = row_stats_fin(sd, lane), v1 = row_stats_fin(sd + 8, lane);
          stats_send(v0, dst, barx(c, B_STB), lane);
          if (warp >= 6) stats_send(v1, dst + 384, barx(c, B_STB), lane);
        }
        if (layer == 0 && wg < 2) {
          bwait(c, B_FULL + 32 + wg, 0);
          const uint32_t a = c.sb + OFF_RING + (2 + 2 * wg + (w >> 1)) * RSLOT + ((w & 1) * 16 + (mi & 1) * 8 + r8) * 144 + (mi >> 1) * 16;
#pragma unroll
          for (int j = 0; j < 8; j += 2) ldsm4(&yf[j][0], a + j * 16);
          ldsm2(&yf[8][0], a + 128);
          __syncwarp();
          if (l0) mbar_arrive_n(barx(c, B_EMPTY + 2 + 2 * wg + (w >> 1)), 6);
        }
        if (threadIdx.x >= 240) {
          const int r = threadIdx.x - 240;
          bwait_cl(c, B_STB, layer);
          const float2 v = finish_stats(c.sb + OFF_STB + r * 8, 1152);
          sts64f(c.sb + OFF_MRB + r * 8, v.x, v.y);
          if (r == 0) mbar_expect(barx(c, B_STB), 8 * 1152);
        }
        bar_sync(4, 384);
        ST(7);
        if (wg < 2) {
          const uint32_t mrb = c.sb + OFF_MRB + wg * 576 + t * 16;
          float4 m[9];
#pragma unroll
          for (int j = 0; j < 9; j++) m[j] = lds128f(mrb + j * 64);
#pragma unroll
          for (int j = 0; j < 9; j++) {
            xr[j][0] = pack2(fmaf((acc[j * 4 + 0] + m[j].y) * m[j].x, bflo(yf[j][0]), acc[j * 4 + 0]),
                             fmaf((acc[j * 4 + 1] + m[j].w) * m[j].z, bfhi(yf[j][0]), acc[j * 4 + 1]));
            xr[j][1] = pack2(fmaf((acc[j * 4 + 2] + m[j].y) * m[j].x, bflo(yf[j][1]), acc[j * 4 + 2]),
                             fmaf((acc[j * 4 + 3] + m[j].w) * m[j].z, bfhi(yf[j][1]), acc[j * 4 + 3]));
          }
#pragma unroll
          for (int j = 0; j < 8; j += 2) stsm4t(sta + j * 256, xr[j][0], xr[j][1], xr[j + 1][0], xr[j + 1][1]);
          stsm2t(sta + 2048, xr[8][0], xr[8][1]);
          fence_async_smem();
          __syncwarp();
          if (l0) mbar_arrive_n(barx(c, B_STAGED), 1 + (w & 1));
        }
      }
      ST(8);
    }
    bwait(c, B_STAGED, 1);
#pragma unroll
    for (int k = 0; k < 3; k++) {
      const int unit = warp * 3 + k;
      const int grp = unit >> 1, chunk = (unit & 1) * 4 + mi;
      const uint4 v = lds128(own + (chunk >> 1) * SUBT + 256 + grp * 256 + (chunk & 1) * 128 + r8 * 16);
      const int ci = ciA + grp * 8 + r8;
      if (grp > 0 || tile == 0)
        *(uint4*)(outp + (size_t)(ci & 1023) * 1024 + (ci >> 10) * 512 + rank * 64 + chunk * 8) = v;
    }
    { const int layer = 1; ST(9); }
  }
}

typedef CUresult (*EncFn)(CUtensorMap*, CUtensorMapDataType, cuuint32_t, void*, const cuuint64_t*, const cuuint64_t*,
                          const cuuint32_t*, const cuuint32_t*, CUtensorMapInterleave, CUtensorMapSwizzle,
                          CUtensorMapL2promotion, CUtensorMapFloatOOBfill);

static void enc2d(EncFn fn, CUtensorMap* tm, const void* base, uint64_t w, uint64_t h, uint32_t bw, uint32_t bh, bool swz) {
  cuuint64_t gd[2] = {w, h};
  cuuint64_t gs[1] = {w * 2};
  cuuint32_t bd[2] = {bw, bh};
  cuuint32_t es[2] = {1, 1};
  fn(tm, CU_TENSOR_MAP_DATA_TYPE_BFLOAT16, 2, const_cast<void*>(base), gd, gs, bd, es, CU_TENSOR_MAP_INTERLEAVE_NONE,
     swz ? CU_TENSOR_MAP_SWIZZLE_128B : CU_TENSOR_MAP_SWIZZLE_NONE, CU_TENSOR_MAP_L2_PROMOTION_L2_128B,
     CU_TENSOR_MAP_FLOAT_OOB_FILL_NONE);
}

extern "C" void kernel_launch(void* const* d_in, const int* in_sizes, int n_in, void* d_out, int out_size) {
  const __nv_bfloat16* x = (const __nv_bfloat16*)d_in[0];
  const __nv_bfloat16* wqkv = (const __nv_bfloat16*)d_in[1];
  const __nv_bfloat16* wo = (const __nv_bfloat16*)d_in[2];
  const __nv_bfloat16* kp = (const __nv_bfloat16*)d_in[4];
  const __nv_bfloat16* vp = (const __nv_bfloat16*)d_in[5];
  const __nv_bfloat16* shp = (const __nv_bfloat16*)d_in[6];
  const __nv_bfloat16* hp = (const __nv_bfloat16*)d_in[7];
  const __nv_bfloat16* Dp = (const __nv_bfloat16*)d_in[8];

  static EncFn enc = nullptr;
  static void* ybase = nullptr;
  static int fused = 0;
  cudaStream_t st = cudaStreamPerThread;
  cudaLaunchConfig_t cfg = {};
  cfg.gridDim = dim3(NT * 8);
  cfg.blockDim = dim3(512);
  cfg.dynamicSmemBytes = SMEM_MAIN;
  cfg.stream = st;
  if (!enc) {
    void* fn = nullptr;
    cudaDriverEntryPointQueryResult qr;
    cudaGetDriverEntryPoint("cuTensorMapEncodeTiled", &fn, cudaEnableDefault, &qr);
    enc = (EncFn)fn;
    cudaGetSymbolAddress(&ybase, g_Y);
    cudaFuncSetAttribute(main_kernel, cudaFuncAttributeMaxDynamicSharedMemorySize, SMEM_MAIN);
    cudaFuncSetAttribute(side_kernel, cudaFuncAttributeMaxDynamicSharedMemorySize, SMEM_SIDE);
    int ncl = 0, nsm = 0, dev = 0;
    cudaGetDevice(&dev);
    cudaDeviceGetAttribute(&nsm, cudaDevAttrMultiProcessorCount, dev);
    cudaOccupancyMaxActiveClusters(&ncl, main_kernel, &cfg);
    fused = (ncl >= NT && nsm >= NT * 8 + 8) ? 1 : 0;
    (void)cudaGetLastError();
  }
  CUtensorMap tmX72, tmX7, tmW, tmWo, tmY;
  enc2d(enc, &tmX72, x, 1024, 1024, 64, 72, true);
  enc2d(enc, &tmX7, x, 1024, 1024, 64, 7, true);
  enc2d(enc, &tmW, wqkv, 1536, 512, 64, 64, true);
  enc2d(enc, &tmWo, wo, 512, 512, 64, 64, true);
  enc2d(enc, &tmY, ybase, 2048, 512, 72, 32, false);
  __nv_bfloat16* outp = (__nv_bfloat16*)d_out;

  CUtensorMap tmK, tmV;
  for (int i = 0; i < 2; i++) {
    cuuint64_t gd[3] = {512, 256, 8};
    cuuint64_t gs[2] = {8192, 1024};
    cuuint32_t bd[3] = {32, (cuuint32_t)(i ? 16 : 17), 8};
    cuuint32_t es[3] = {1, 1, 1};
    enc(i ? &tmV : &tmK, CU_TENSOR_MAP_DATA_TYPE_BFLOAT16, 3, const_cast<__nv_bfloat16*>(i ? vp : kp), gd, gs, bd, es,
        CU_TENSOR_MAP_INTERLEAVE_NONE, CU_TENSOR_MAP_SWIZZLE_64B, CU_TENSOR_MAP_L2_PROMOTION_L2_128B, CU_TENSOR_MAP_FLOAT_OOB_FILL_NONE);
  }

  if (fused) {
    cudaLaunchKernelEx(&cfg, main_kernel, tmX72, tmX7, tmW, tmWo, tmY, tmK, tmV, outp, wqkv, wo, kp, vp, shp, hp, Dp, 1);
    cudaLaunchConfig_t c2 = {};
    c2.gridDim = dim3(8);
    c2.blockDim = dim3(512);
    c2.dynamicSmemBytes = SMEM_SIDE;
    c2.stream = st;
    cudaLaunchAttribute a2[1];
    a2[0].id = cudaLaunchAttributeProgrammaticStreamSerialization;
    a2[0].val.programmaticStreamSerializationAllowed = 1;
    c2.attrs = a2;
    c2.numAttrs = 1;
    cudaLaunchKernelEx(&c2, side_kernel, tmK, tmV, shp, hp, Dp, 3, 120, 480, 8);
  } else {
    side_kernel<<<128, 512, SMEM_SIDE, st>>>(tmK, tmV, shp, hp, Dp, 1, 0, 0, 0);
    side_kernel<<<128, 512, SMEM_SIDE, st>>>(tmK, tmV, shp, hp, Dp, 2, 0, 0, 0);
    cudaLaunchKernelEx(&cfg, main_kernel, tmX72, tmX7, tmW, tmWo, tmY, tmK, tmV, outp, wqkv, wo, kp, vp, shp, hp, Dp, 0);
  }
}
```

```cpp
#include <cuda_runtime.h>
#include <cuda_bf16.h>
#include <cuda.h>
#include <stdint.h>

#define DEVI __device__ __forceinline__

#define PROFILE 0

namespace {

constexpr int NT = 15;
constexpr int XSLOT = 19456;
constexpr int SUBT = 4864;
constexpr int RSLOT = 8192;
constexpr unsigned PFT = 2300;
constexpr int STAG1 = 300;
constexpr int STAG = 450;
constexpr int NRING = 6;
constexpr int OFF_X = 0;
constexpr int OFF_RING = 8 * XSLOT;
constexpr int OFF_STQ = OFF_RING + NRING * RSLOT;
constexpr int OFF_BAR = OFF_STQ + 8 * 1216;
constexpr int OFF_STB = OFF_BAR + 896;
constexpr int STBP = 1216;
constexpr int OFF_URAW = OFF_STB;
constexpr int OFF_PROF = OFF_URAW + 16384;
constexpr int SMEM_MAIN = OFF_PROF + (PROFILE ? 640 : 0);
static_assert(SMEM_MAIN <= 232448, "smem");

constexpr int UAP = 2320;
constexpr int UCH = 4 * UAP;
constexpr int HCP = 560;
constexpr int KIN = 17 * 8 * 64, VIN = 16 * 8 * 64;
constexpr int KVIN = KIN + VIN + 256;

enum { B_FULL = 0, B_XOWN = 35, B_XFULL = 68, B_KIN = 76, B_VIN, B_URAW, B_STQ, B_STB, B_MRQ, B_KFREE,
       B_OSTORED = 84, B_XFREE, B_KQST, B_CVD,
       B_EMPTY = 91, B_STAGED = 97, B_VDONE, B_TD,
       B_HFREE = B_TD + 4, B_YST, B_TAB = B_YST + 4,
       B_COUNT = B_TAB + 4,
       B_X2ST = B_TD + 2 };
constexpr unsigned OSEQ1 = 0x23715460u;
constexpr unsigned HSLOT = 0x3754u;

}

__device__ __align__(1024) __nv_bfloat16 g_Y[512 * 2048];
__device__ __align__(1024) uint8_t g_exO[NT * 8 * XSLOT];
__device__ __align__(1024) uint8_t g_exX[NT * 8 * XSLOT];
__device__ __align__(1024) __nv_bfloat16 g_U[512 * 2048];
__device__ unsigned g_ycnt[8];
__device__ unsigned g_ucnt;
__device__ unsigned g_done;
#define STAMP(i) do {} while (0)

DEVI uint32_t s2u(const void* p) { return (uint32_t)__cvta_generic_to_shared(p); }
DEVI void mbar_init(uint32_t b, int c) { asm volatile("mbarrier.init.shared::cta.b64 [%0], %1;" ::"r"(b), "r"(c) : "memory"); }
DEVI void mbar_expect(uint32_t b, uint32_t bytes) {
  asm volatile("mbarrier.arrive.expect_tx.shared::cta.b64 _, [%0], %1;" ::"r"(b), "r"(bytes) : "memory");
}
DEVI void mbar_arrive(uint32_t b) { asm volatile("mbarrier.arrive.shared::cta.b64 _, [%0];" ::"r"(b) : "memory"); }
DEVI void mbar_arrive_n(uint32_t b, int n) { asm volatile("mbarrier.arrive.shared::cta.b64 _, [%0], %1;" ::"r"(b), "r"(n) : "memory"); }
DEVI void mbar_arrive_remote(uint32_t b) {
  asm volatile("mbarrier.arrive.relaxed.cluster.shared::cluster.b64 _, [%0];" ::"r"(b) : "memory");
}
DEVI uint32_t clk32() { uint32_t t; asm volatile("mov.u32 %0,%%clock;" : "=r"(t)); return t; }
DEVI bool expired(uint32_t t0) { return clk32() - t0 > (1u << 28); }
DEVI void mbar_wait(uint32_t b, uint32_t ph, uint32_t t0) {
  uint32_t ok;
  do {
    asm volatile("{.reg .pred p; mbarrier.try_wait.parity.shared::cta.b64 p,[%1],%2; selp.u32 %0,1,0,p;}"
                 : "=r"(ok) : "r"(b), "r"(ph) : "memory");
  } while (!ok && !expired(t0));
}
DEVI bool mbar_test(uint32_t b, uint32_t ph) {
  uint32_t ok;
  asm volatile("{.reg .pred p; mbarrier.test_wait.parity.shared::cta.b64 p,[%1],%2; selp.u32 %0,1,0,p;}"
               : "=r"(ok) : "r"(b), "r"(ph) : "memory");
  return ok;
}
DEVI uint32_t mapa(uint32_t a, uint32_t r) {
  uint32_t o;
  asm("mapa.shared::cluster.u32 %0,%1,%2;" : "=r"(o) : "r"(a), "r"(r));
  return o;
}
DEVI void fence_async_smem() { asm volatile("fence.proxy.async.shared::cta;" ::: "memory"); }
DEVI void reads_done() { asm volatile("fence.acq_rel.cta;" ::: "memory"); }
DEVI void bar_sync(int id, int n) { __syncwarp(); asm volatile("bar.sync %0,%1;" ::"r"(id), "r"(n) : "memory"); }
DEVI void bar_arrive(int id, int n) { __syncwarp(); asm volatile("bar.arrive %0,%1;" ::"r"(id), "r"(n) : "memory"); }
DEVI void tma2d(uint32_t dst, const CUtensorMap* tm, int x, int y, uint32_t bar) {
  asm volatile("cp.async.bulk.tensor.2d.shared::cluster.global.mbarrier::complete_tx::bytes [%0],[%1,{%3,%4}],[%2];"
               ::"r"(dst), "l"(tm), "r"(bar), "r"(x), "r"(y) : "memory");
}
DEVI void tma3d(uint32_t dst, const CUtensorMap* tm, int x, int y, int z, uint32_t bar) {
  asm volatile("cp.async.bulk.tensor.3d.shared::cluster.global.mbarrier::complete_tx::bytes [%0],[%1,{%3,%4,%5}],[%2];"
               ::"r"(dst), "l"(tm), "r"(bar), "r"(x), "r"(y), "r"(z) : "memory");
}
DEVI void flag_wait(const unsigned* p, unsigned target, uint32_t t0) {
  unsigned v;
  while (true) {
    asm volatile("ld.relaxed.gpu.global.u32 %0,[%1];" : "=r"(v) : "l"(p) : "memory");
    if (v >= target || expired(t0)) break;
    __nanosleep(40);
  }
}
DEVI void tma2d_mc(uint32_t dst, const CUtensorMap* tm, int x, int y, uint32_t bar, uint16_t mask) {
  asm volatile("cp.async.bulk.tensor.2d.shared::cluster.global.mbarrier::complete_tx::bytes.multicast::cluster [%0],[%1,{%3,%4}],[%2],%5;"
               ::"r"(dst), "l"(tm), "r"(bar), "r"(x), "r"(y), "h"(mask) : "memory");
}
DEVI void bulk_load(uint32_t dst, const void* src, uint32_t bytes, uint32_t bar) {
  asm volatile("cp.async.bulk.shared::cluster.global.mbarrier::complete_tx::bytes [%0],[%1],%2,[%3];"
               ::"r"(dst), "l"(src), "r"(bytes), "r"(bar) : "memory");
}
DEVI void bulk_load_mc(uint32_t dst, const void* src, uint32_t bytes, uint32_t bar, uint16_t mask) {
  asm volatile("cp.async.bulk.shared::cluster.global.mbarrier::complete_tx::bytes.multicast::cluster [%0],[%1],%2,[%3],%4;"
               ::"r"(dst), "l"(src), "r"(bytes), "r"(bar), "h"(mask) : "memory");
}
DEVI void bulk_s2s(uint32_t dst, uint32_t src, uint32_t bytes, uint32_t bar) {
  asm volatile("cp.async.bulk.shared::cluster.shared::cta.mbarrier::complete_tx::bytes [%0],[%1],%2,[%3];"
               ::"r"(dst), "r"(src), "r"(bytes), "r"(bar) : "memory");
}
DEVI void bulk_store(void* dst, uint32_t src, uint32_t bytes) {
  asm volatile("cp.async.bulk.global.shared::cta.bulk_group [%0],[%1],%2;" ::"l"(dst), "r"(src), "r"(bytes) : "memory");
}
DEVI void bulk_commit() { asm volatile("cp.async.bulk.commit_group;" ::: "memory"); }
DEVI void bulk_wait0() { asm volatile("cp.async.bulk.wait_group 0;" ::: "memory"); }
template <int N> DEVI void bulk_wait() { asm volatile("cp.async.bulk.wait_group %0;" ::"n"(N) : "memory"); }
DEVI void st_async2(uint32_t dst, float a, float b, uint32_t bar) {
  asm volatile("st.async.weak.shared::cluster.mbarrier::complete_tx::bytes.v2.f32 [%0],{%1,%2},[%3];"
               ::"r"(dst), "f"(a), "f"(b), "r"(bar) : "memory");
}
DEVI void st_async4(uint32_t dst, uint32_t a, uint32_t b, uint32_t c, uint32_t d, uint32_t bar) {
  asm volatile("st.async.weak.shared::cluster.mbarrier::complete_tx::bytes.v4.b32 [%0],{%1,%2,%3,%4},[%5];"
               ::"r"(dst), "r"(a), "r"(b), "r"(c), "r"(d), "r"(bar) : "memory");
}
DEVI void wg_fence() { asm volatile("wgmma.fence.sync.aligned;" ::: "memory"); }
DEVI void wg_commit() { asm volatile("wgmma.commit_group.sync.aligned;" ::: "memory"); }
template <int N> DEVI void wg_wait() { asm volatile("wgmma.wait_group.sync.aligned %0;" ::"n"(N) : "memory"); }
DEVI uint64_t desc64(uint32_t lo, uint32_t hi) {
  uint64_t d;
  asm("mov.b64 %0,{%1,%2};" : "=l"(d) : "r"(lo), "r"(hi));
  return d;
}
DEVI uint32_t pin(uint32_t v) { asm volatile("" : "+r"(v)); return v; }
DEVI bool elect() {
  uint32_t p;
  asm volatile("{.reg .pred p; elect.sync _|p,0xffffffff; selp.u32 %0,1,0,p;}" : "=r"(p));
  return p;
}
DEVI int uni(int v) { return __shfl_sync(~0u, v, 0); }
DEVI void mma16816(float* c, uint32_t a0, uint32_t a1, uint32_t a2, uint32_t a3, uint32_t b0, uint32_t b1) {
  asm volatile("mma.sync.aligned.m16n8k16.row.col.f32.bf16.bf16.f32 {%0,%1,%2,%3},{%4,%5,%6,%7},{%8,%9},{%0,%1,%2,%3};"
               : "+f"(c[0]), "+f"(c[1]), "+f"(c[2]), "+f"(c[3]) : "r"(a0), "r"(a1), "r"(a2), "r"(a3), "r"(b0), "r"(b1));
}
DEVI void mma16816_z(float* c, uint32_t a0, uint32_t a1, uint32_t a2, uint32_t a3, uint32_t b0, uint32_t b1) {
  asm volatile("mma.sync.aligned.m16n8k16.row.col.f32.bf16.bf16.f32 {%0,%1,%2,%3},{%4,%5,%6,%7},{%8,%9},{%10,%10,%10,%10};"
               : "=f"(c[0]), "=f"(c[1]), "=f"(c[2]), "=f"(c[3]) : "r"(a0), "r"(a1), "r"(a2), "r"(a3), "r"(b0), "r"(b1), "f"(0.f));
}
DEVI uint32_t pack2(float lo, float hi) {
  uint32_t r;
  asm("cvt.rn.bf16x2.f32 %0,%1,%2;" : "=r"(r) : "f"(hi), "f"(lo));
  return r;
}
DEVI float bflo(uint32_t v) { return __uint_as_float(v << 16); }
DEVI float bfhi(uint32_t v) { return __uint_as_float(v & 0xffff0000u); }
DEVI void ldsm4(uint32_t* r, uint32_t a) {
  asm volatile("ldmatrix.sync.aligned.m8n8.x4.shared.b16 {%0,%1,%2,%3},[%4];" : "=r"(r[0]), "=r"(r[1]), "=r"(r[2]), "=r"(r[3]) : "r"(a) : "memory");
}
DEVI void ldsm4t(uint32_t* r, uint32_t a) {
  asm volatile("ldmatrix.sync.aligned.m8n8.x4.trans.shared.b16 {%0,%1,%2,%3},[%4];" : "=r"(r[0]), "=r"(r[1]), "=r"(r[2]), "=r"(r[3]) : "r"(a) : "memory");
}
DEVI void ldsm2t(uint32_t* r, uint32_t a) {
  asm volatile("ldmatrix.sync.aligned.m8n8.x2.trans.shared.b16 {%0,%1},[%2];" : "=r"(r[0]), "=r"(r[1]) : "r"(a) : "memory");
}
DEVI void stsm4t(uint32_t a, uint32_t r0, uint32_t r1, uint32_t r2, uint32_t r3) {
  asm volatile("stmatrix.sync.aligned.m8n8.x4.trans.shared.b16 [%0],{%1,%2,%3,%4};" ::"r"(a), "r"(r0), "r"(r1), "r"(r2), "r"(r3) : "memory");
}
DEVI void stsm4(uint32_t a, uint32_t r0, uint32_t r1, uint32_t r2, uint32_t r3) {
  asm volatile("stmatrix.sync.aligned.m8n8.x4.shared.b16 [%0],{%1,%2,%3,%4};" ::"r"(a), "r"(r0), "r"(r1), "r"(r2), "r"(r3) : "memory");
}
DEVI void stsm2t(uint32_t a, uint32_t r0, uint32_t r1) {
  asm volatile("stmatrix.sync.aligned.m8n8.x2.trans.shared.b16 [%0],{%1,%2};" ::"r"(a), "r"(r0), "r"(r1) : "memory");
}
DEVI uint32_t lds32(uint32_t a) { uint32_t v; asm volatile("ld.shared.u32 %0,[%1];" : "=r"(v) : "r"(a) : "memory"); return v; }
DEVI float2 lds64f(uint32_t a) { float2 v; asm volatile("ld.shared.v2.f32 {%0,%1},[%2];" : "=f"(v.x), "=f"(v.y) : "r"(a) : "memory"); return v; }
DEVI uint4 lds128(uint32_t a) {
  uint4 v;
  asm volatile("ld.shared.v4.u32 {%0,%1,%2,%3},[%4];" : "=r"(v.x), "=r"(v.y), "=r"(v.z), "=r"(v.w) : "r"(a) : "memory");
  return v;
}
DEVI void sts16(uint32_t a, uint32_t v) { asm volatile("st.shared.u16 [%0],%1;" ::"r"(a), "h"((uint16_t)v) : "memory"); }
DEVI void sts32(uint32_t a, uint32_t v) { asm volatile("st.shared.u32 [%0],%1;" ::"r"(a), "r"(v) : "memory"); }
DEVI void sts64f(uint32_t a, float x, float y) { asm volatile("st.shared.v2.f32 [%0],{%1,%2};" ::"r"(a), "f"(x), "f"(y) : "memory"); }
DEVI void sts128(uint32_t a, uint32_t x, uint32_t y, uint32_t z, uint32_t w) {
  asm volatile("st.shared.v4.u32 [%0],{%1,%2,%3,%4};" ::"r"(a), "r"(x), "r"(y), "r"(z), "r"(w) : "memory");
}
DEVI uint32_t hfma2(uint32_t a, uint32_t b, uint32_t c) { uint32_t d; asm("fma.rn.bf16x2 %0,%1,%2,%3;" : "=r"(d) : "r"(a), "r"(b), "r"(c)); return d; }
DEVI uint32_t hmul2(uint32_t a, uint32_t b) { uint32_t d; asm("mul.rn.bf16x2 %0,%1,%2;" : "=r"(d) : "r"(a), "r"(b)); return d; }
DEVI float ex2(float x) { float y; asm("ex2.approx.ftz.f32 %0,%1;" : "=f"(y) : "f"(x)); return y; }
DEVI float rcp(float x) { float y; asm("rcp.approx.ftz.f32 %0,%1;" : "=f"(y) : "f"(x)); return y; }

__device__ __forceinline__ void conv_mma(float* d, uint32_t da, uint32_t db) {
  asm volatile(
   "{.reg .pred p0,p1; .reg .b64 a,b; .reg .b32 x,y,ha,hb;\n"
   "setp.ne.b32 p0,0,0; setp.eq.b32 p1,0,0; mov.b32 ha,35; mov.b32 hb,8;\n"
   "wgmma.fence.sync.aligned;\n"
   "add.u32 x,%64,0; add.u32 y,%65,0; mov.b64 a,{x,ha}; mov.b64 b,{y,hb};\n"
   "wgmma.mma_async.sync.aligned.m64n128k16.f32.bf16.bf16 {%0,%1,%2,%3,%4,%5,%6,%7,%8,%9,%10,%11,%12,%13,%14,%15,%16,%17,%18,%19,%20,%21,%22,%23,%24,%25,%26,%27,%28,%29,%30,%31,%32,%33,%34,%35,%36,%37,%38,%39,%40,%41,%42,%43,%44,%45,%46,%47,%48,%49,%50,%51,%52,%53,%54,%55,%56,%57,%58,%59,%60,%61,%62,%63},a,b,p0,1,1,0,0;\n"
   "add.u32 x,%64,2; add.u32 y,%65,290; mov.b64 a,{x,ha}; mov.b64 b,{y,hb};\n"
   "wgmma.mma_async.sync.aligned.m64n128k16.f32.bf16.bf16 {%0,%1,%2,%3,%4,%5,%6,%7,%8,%9,%10,%11,%12,%13,%14,%15,%16,%17,%18,%19,%20,%21,%22,%23,%24,%25,%26,%27,%28,%29,%30,%31,%32,%33,%34,%35,%36,%37,%38,%39,%40,%41,%42,%43,%44,%45,%46,%47,%48,%49,%50,%51,%52,%53,%54,%55,%56,%57,%58,%59,%60,%61,%62,%63},a,b,p1,1,1,0,0;\n"
   "add.u32 x,%64,8; add.u32 y,%65,4; mov.b64 a,{x,ha}; mov.b64 b,{y,hb};\n"
   "wgmma.mma_async.sync.aligned.m64n128k16.f32.bf16.bf16 {%0,%1,%2,%3,%4,%5,%6,%7,%8,%9,%10,%11,%12,%13,%14,%15,%16,%17,%18,%19,%20,%21,%22,%23,%24,%25,%26,%27,%28,%29,%30,%31,%32,%33,%34,%35,%36,%37,%38,%39,%40,%41,%42,%43,%44,%45,%46,%47,%48,%49,%50,%51,%52,%53,%54,%55,%56,%57,%58,%59,%60,%61,%62,%63},a,b,p1,1,1,0,0;\n"
   "add.u32 x,%64,10; add.u32 y,%65,294; mov.b64 a,{x,ha}; mov.b64 b,{y,hb};\n"
   "wgmma.mma_async.sync.aligned.m64n128k16.f32.bf16.bf16 {%0,%1,%2,%3,%4,%5,%6,%7,%8,%9,%10,%11,%12,%13,%14,%15,%16,%17,%18,%19,%20,%21,%22,%23,%24,%25,%26,%27,%28,%29,%30,%31,%32,%33,%34,%35,%36,%37,%38,%39,%40,%41,%42,%43,%44,%45,%46,%47,%48,%49,%50,%51,%52,%53,%54,%55,%56,%57,%58,%59,%60,%61,%62,%63},a,b,p1,1,1,0,0;\n"
   "add.u32 x,%64,16; add.u32 y,%65,8; mov.b64 a,{x,ha}; mov.b64 b,{y,hb};\n"
   "wgmma.mma_async.sync.aligned.m64n128k16.f32.bf16.bf16 {%0,%1,%2,%3,%4,%5,%6,%7,%8,%9,%10,%11,%12,%13,%14,%15,%16,%17,%18,%19,%20,%21,%22,%23,%24,%25,%26,%27,%28,%29,%30,%31,%32,%33,%34,%35,%36,%37,%38,%39,%40,%41,%42,%43,%44,%45,%46,%47,%48,%49,%50,%51,%52,%53,%54,%55,%56,%57,%58,%59,%60,%61,%62,%63},a,b,p1,1,1,0,0;\n"
   "add.u32 x,%64,18; add.u32 y,%65,298; mov.b64 a,{x,ha}; mov.b64 b,{y,hb};\n"
   "wgmma.mma_async.sync.aligned.m64n128k16.f32.bf16.bf16 {%0,%1,%2,%3,%4,%5,%6,%7,%8,%9,%10,%11,%12,%13,%14,%15,%16,%17,%18,%19,%20,%21,%22,%23,%24,%25,%26,%27,%28,%29,%30,%31,%32,%33,%34,%35,%36,%37,%38,%39,%40,%41,%42,%43,%44,%45,%46,%47,%48,%49,%50,%51,%52,%53,%54,%55,%56,%57,%58,%59,%60,%61,%62,%63},a,b,p1,1,1,0,0;\n"
   "add.u32 x,%64,24; add.u32 y,%65,12; mov.b64 a,{x,ha}; mov.b64 b,{y,hb};\n"
   "wgmma.mma_async.sync.aligned.m64n128k16.f32.bf16.bf16 {%0,%1,%2,%3,%4,%5,%6,%7,%8,%9,%10,%11,%12,%13,%14,%15,%16,%17,%18,%19,%20,%21,%22,%23,%24,%25,%26,%27,%28,%29,%30,%31,%32,%33,%34,%35,%36,%37,%38,%39,%40,%41,%42,%43,%44,%45,%46,%47,%48,%49,%50,%51,%52,%53,%54,%55,%56,%57,%58,%59,%60,%61,%62,%63},a,b,p1,1,1,0,0;\n"
   "add.u32 x,%64,26; add.u32 y,%65,302; mov.b64 a,{x,ha}; mov.b64 b,{y,hb};\n"
   "wgmma.mma_async.sync.aligned.m64n128k16.f32.bf16.bf16 {%0,%1,%2,%3,%4,%5,%6,%7,%8,%9,%10,%11,%12,%13,%14,%15,%16,%17,%18,%19,%20,%21,%22,%23,%24,%25,%26,%27,%28,%29,%30,%31,%32,%33,%34,%35,%36,%37,%38,%39,%40,%41,%42,%43,%44,%45,%46,%47,%48,%49,%50,%51,%52,%53,%54,%55,%56,%57,%58,%59,%60,%61,%62,%63},a,b,p1,1,1,0,0;\n"
   "wgmma.commit_group.sync.aligned;\n"
   "wgmma.wait_group.sync.aligned 0;\n"
   "add.u32 x,%64,280; add.u32 y,%65,32; mov.b64 a,{x,ha}; mov.b64 b,{y,hb};\n"
   "wgmma.mma_async.sync.aligned.m64n96k16.f32.bf16.bf16 {%0,%1,%2,%3,%4,%5,%6,%7,%8,%9,%10,%11,%12,%13,%14,%15,%16,%17,%18,%19,%20,%21,%22,%23,%24,%25,%26,%27,%28,%29,%30,%31,%32,%33,%34,%35,%36,%37,%38,%39,%40,%41,%42,%43,%44,%45,%46,%47},a,b,p1,1,1,0,0;\n"
   "add.u32 x,%64,282; add.u32 y,%65,322; mov.b64 a,{x,ha}; mov.b64 b,{y,hb};\n"
   "wgmma.mma_async.sync.aligned.m64n96k16.f32.bf16.bf16 {%0,%1,%2,%3,%4,%5,%6,%7,%8,%9,%10,%11,%12,%13,%14,%15,%16,%17,%18,%19,%20,%21,%22,%23,%24,%25,%26,%27,%28,%29,%30,%31,%32,%33,%34,%35,%36,%37,%38,%39,%40,%41,%42,%43,%44,%45,%46,%47},a,b,p1,1,1,0,0;\n"
   "add.u32 x,%64,288; add.u32 y,%65,36; mov.b64 a,{x,ha}; mov.b64 b,{y,hb};\n"
   "wgmma.mma_async.sync.aligned.m64n96k16.f32.bf16.bf16 {%0,%1,%2,%3,%4,%5,%6,%7,%8,%9,%10,%11,%12,%13,%14,%15,%16,%17,%18,%19,%20,%21,%22,%23,%24,%25,%26,%27,%28,%29,%30,%31,%32,%33,%34,%35,%36,%37,%38,%39,%40,%41,%42,%43,%44,%45,%46,%47},a,b,p1,1,1,0,0;\n"
   "add.u32 x,%64,290; add.u32 y,%65,326; mov.b64 a,{x,ha}; mov.b64 b,{y,hb};\n"
   "wgmma.mma_async.sync.aligned.m64n96k16.f32.bf16.bf16 {%0,%1,%2,%3,%4,%5,%6,%7,%8,%9,%10,%11,%12,%13,%14,%15,%16,%17,%18,%19,%20,%21,%22,%23,%24,%25,%26,%27,%28,%29,%30,%31,%32,%33,%34,%35,%36,%37,%38,%39,%40,%41,%42,%43,%44,%45,%46,%47},a,b,p1,1,1,0,0;\n"
   "add.u32 x,%64,296; add.u32 y,%65,40; mov.b64 a,{x,ha}; mov.b64 b,{y,hb};\n"
   "wgmma.mma_async.sync.aligned.m64n96k16.f32.bf16.bf16 {%0,%1,%2,%3,%4,%5,%6,%7,%8,%9,%10,%11,%12,%13,%14,%15,%16,%17,%18,%19,%20,%21,%22,%23,%24,%25,%26,%27,%28,%29,%30,%31,%32,%33,%34,%35,%36,%37,%38,%39,%40,%41,%42,%43,%44,%45,%46,%47},a,b,p1,1,1,0,0;\n"
   "add.u32 x,%64,298; add.u32 y,%65,330; mov.b64 a,{x,ha}; mov.b64 b,{y,hb};\n"
   "wgmma.mma_async.sync.aligned.m64n96k16.f32.bf16.bf16 {%0,%1,%2,%3,%4,%5,%6,%7,%8,%9,%10,%11,%12,%13,%14,%15,%16,%17,%18,%19,%20,%21,%22,%23,%24,%25,%26,%27,%28,%29,%30,%31,%32,%33,%34,%35,%36,%37,%38,%39,%40,%41,%42,%43,%44,%45,%46,%47},a,b,p1,1,1,0,0;\n"
   "add.u32 x,%64,304; add.u32 y,%65,44; mov.b64 a,{x,ha}; mov.b64 b,{y,hb};\n"
   "wgmma.mma_async.sync.aligned.m64n96k16.f32.bf16.bf16 {%0,%1,%2,%3,%4,%5,%6,%7,%8,%9,%10,%11,%12,%13,%14,%15,%16,%17,%18,%19,%20,%21,%22,%23,%24,%25,%26,%27,%28,%29,%30,%31,%32,%33,%34,%35,%36,%37,%38,%39,%40,%41,%42,%43,%44,%45,%46,%47},a,b,p1,1,1,0,0;\n"
   "add.u32 x,%64,306; add.u32 y,%65,334; mov.b64 a,{x,ha}; mov.b64 b,{y,hb};\n"
   "wgmma.mma_async.sync.aligned.m64n96k16.f32.bf16.bf16 {%0,%1,%2,%3,%4,%5,%6,%7,%8,%9,%10,%11,%12,%13,%14,%15,%16,%17,%18,%19,%20,%21,%22,%23,%24,%25,%26,%27,%28,%29,%30,%31,%32,%33,%34,%35,%36,%37,%38,%39,%40,%41,%42,%43,%44,%45,%46,%47},a,b,p1,1,1,0,0;\n"
   "wgmma.commit_group.sync.aligned;\n"
   "wgmma.wait_group.sync.aligned 0;\n"
   "add.u32 x,%64,560; add.u32 y,%65,64; mov.b64 a,{x,ha}; mov.b64 b,{y,hb};\n"
   "wgmma.mma_async.sync.aligned.m64n64k16.f32.bf16.bf16 {%0,%1,%2,%3,%4,%5,%6,%7,%8,%9,%10,%11,%12,%13,%14,%15,%16,%17,%18,%19,%20,%21,%22,%23,%24,%25,%26,%27,%28,%29,%30,%31},a,b,p1,1,1,0,0;\n"
   "add.u32 x,%64,562; add.u32 y,%65,354; mov.b64 a,{x,ha}; mov.b64 b,{y,hb};\n"
   "wgmma.mma_async.sync.aligned.m64n64k16.f32.bf16.bf16 {%0,%1,%2,%3,%4,%5,%6,%7,%8,%9,%10,%11,%12,%13,%14,%15,%16,%17,%18,%19,%20,%21,%22,%23,%24,%25,%26,%27,%28,%29,%30,%31},a,b,p1,1,1,0,0;\n"
   "add.u32 x,%64,568; add.u32 y,%65,68; mov.b64 a,{x,ha}; mov.b64 b,{y,hb};\n"
   "wgmma.mma_async.sync.aligned.m64n64k16.f32.bf16.bf16 {%0,%1,%2,%3,%4,%5,%6,%7,%8,%9,%10,%11,%12,%13,%14,%15,%16,%17,%18,%19,%20,%21,%22,%23,%24,%25,%26,%27,%28,%29,%30,%31},a,b,p1,1,1,0,0;\n"
   "add.u32 x,%64,570; add.u32 y,%65,358; mov.b64 a,{x,ha}; mov.b64 b,{y,hb};\n"
   "wgmma.mma_async.sync.aligned.m64n64k16.f32.bf16.bf16 {%0,%1,%2,%3,%4,%5,%6,%7,%8,%9,%10,%11,%12,%13,%14,%15,%16,%17,%18,%19,%20,%21,%22,%23,%24,%25,%26,%27,%28,%29,%30,%31},a,b,p1,1,1,0,0;\n"
   "add.u32 x,%64,576; add.u32 y,%65,72; mov.b64 a,{x,ha}; mov.b64 b,{y,hb};\n"
   "wgmma.mma_async.sync.aligned.m64n64k16.f32.bf16.bf16 {%0,%1,%2,%3,%4,%5,%6,%7,%8,%9,%10,%11,%12,%13,%14,%15,%16,%17,%18,%19,%20,%21,%22,%23,%24,%25,%26,%27,%28,%29,%30,%31},a,b,p1,1,1,0,0;\n"
   "add.u32 x,%64,578; add.u32 y,%65,362; mov.b64 a,{x,ha}; mov.b64 b,{y,hb};\n"
   "wgmma.mma_async.sync.aligned.m64n64k16.f32.bf16.bf16 {%0,%1,%2,%3,%4,%5,%6,%7,%8,%9,%10,%11,%12,%13,%14,%15,%16,%17,%18,%19,%20,%21,%22,%23,%24,%25,%26,%27,%28,%29,%30,%31},a,b,p1,1,1,0,0;\n"
   "add.u32 x,%64,584; add.u32 y,%65,76; mov.b64 a,{x,ha}; mov.b64 b,{y,hb};\n"
   "wgmma.mma_async.sync.aligned.m64n64k16.f32.bf16.bf16 {%0,%1,%2,%3,%4,%5,%6,%7,%8,%9,%10,%11,%12,%13,%14,%15,%16,%17,%18,%19,%20,%21,%22,%23,%24,%25,%26,%27,%28,%29,%30,%31},a,b,p1,1,1,0,0;\n"
   "add.u32 x,%64,586; add.u32 y,%65,366; mov.b64 a,{x,ha}; mov.b64 b,{y,hb};\n"
   "wgmma.mma_async.sync.aligned.m64n64k16.f32.bf16.bf16 {%0,%1,%2,%3,%4,%5,%6,%7,%8,%9,%10,%11,%12,%13,%14,%15,%16,%17,%18,%19,%20,%21,%22,%23,%24,%25,%26,%27,%28,%29,%30,%31},a,b,p1,1,1,0,0;\n"
   "wgmma.commit_group.sync.aligned;\n"
   "wgmma.wait_group.sync.aligned 0;\n"
   "add.u32 x,%64,840; add.u32 y,%65,96; mov.b64 a,{x,ha}; mov.b64 b,{y,hb};\n"
   "wgmma.mma_async.sync.aligned.m64n32k16.f32.bf16.bf16 {%0,%1,%2,%3,%4,%5,%6,%7,%8,%9,%10,%11,%12,%13,%14,%15},a,b,p1,1,1,0,0;\n"
   "add.u32 x,%64,842; add.u32 y,%65,386; mov.b64 a,{x,ha}; mov.b64 b,{y,hb};\n"
   "wgmma.mma_async.sync.aligned.m64n32k16.f32.bf16.bf16 {%0,%1,%2,%3,%4,%5,%6,%7,%8,%9,%10,%11,%12,%13,%14,%15},a,b,p1,1,1,0,0;\n"
   "add.u32 x,%64,848; add.u32 y,%65,100; mov.b64 a,{x,ha}; mov.b64 b,{y,hb};\n"
   "wgmma.mma_async.sync.aligned.m64n32k16.f32.bf16.bf16 {%0,%1,%2,%3,%4,%5,%6,%7,%8,%9,%10,%11,%12,%13,%14,%15},a,b,p1,1,1,0,0;\n"
   "add.u32 x,%64,850; add.u32 y,%65,390; mov.b64 a,{x,ha}; mov.b64 b,{y,hb};\n"
   "wgmma.mma_async.sync.aligned.m64n32k16.f32.bf16.bf16 {%0,%1,%2,%3,%4,%5,%6,%7,%8,%9,%10,%11,%12,%13,%14,%15},a,b,p1,1,1,0,0;\n"
   "add.u32 x,%64,856; add.u32 y,%65,104; mov.b64 a,{x,ha}; mov.b64 b,{y,hb};\n"
   "wgmma.mma_async.sync.aligned.m64n32k16.f32.bf16.bf16 {%0,%1,%2,%3,%4,%5,%6,%7,%8,%9,%10,%11,%12,%13,%14,%15},a,b,p1,1,1,0,0;\n"
   "add.u32 x,%64,858; add.u32 y,%65,394; mov.b64 a,{x,ha}; mov.b64 b,{y,hb};\n"
   "wgmma.mma_async.sync.aligned.m64n32k16.f32.bf16.bf16 {%0,%1,%2,%3,%4,%5,%6,%7,%8,%9,%10,%11,%12,%13,%14,%15},a,b,p1,1,1,0,0;\n"
   "add.u32 x,%64,864; add.u32 y,%65,108; mov.b64 a,{x,ha}; mov.b64 b,{y,hb};\n"
   "wgmma.mma_async.sync.aligned.m64n32k16.f32.bf16.bf16 {%0,%1,%2,%3,%4,%5,%6,%7,%8,%9,%10,%11,%12,%13,%14,%15},a,b,p1,1,1,0,0;\n"
   "add.u32 x,%64,866; add.u32 y,%65,398; mov.b64 a,{x,ha}; mov.b64 b,{y,hb};\n"
   "wgmma.mma_async.sync.aligned.m64n32k16.f32.bf16.bf16 {%0,%1,%2,%3,%4,%5,%6,%7,%8,%9,%10,%11,%12,%13,%14,%15},a,b,p1,1,1,0,0;\n"
   "wgmma.commit_group.sync.aligned;\n"
   "wgmma.wait_group.sync.aligned 0;\n"
   "}\n"
   :"=f"(d[0]),"=f"(d[1]),"=f"(d[2]),"=f"(d[3]),"=f"(d[4]),"=f"(d[5]),"=f"(d[6]),"=f"(d[7]),"=f"(d[8]),"=f"(d[9]),"=f"(d[10]),"=f"(d[11]),"=f"(d[12]),"=f"(d[13]),"=f"(d[14]),"=f"(d[15]),"=f"(d[16]),"=f"(d[17]),"=f"(d[18]),"=f"(d[19]),"=f"(d[20]),"=f"(d[21]),"=f"(d[22]),"=f"(d[23]),"=f"(d[24]),"=f"(d[25]),"=f"(d[26]),"=f"(d[27]),"=f"(d[28]),"=f"(d[29]),"=f"(d[30]),"=f"(d[31]),"=f"(d[32]),"=f"(d[33]),"=f"(d[34]),"=f"(d[35]),"=f"(d[36]),"=f"(d[37]),"=f"(d[38]),"=f"(d[39]),"=f"(d[40]),"=f"(d[41]),"=f"(d[42]),"=f"(d[43]),"=f"(d[44]),"=f"(d[45]),"=f"(d[46]),"=f"(d[47]),"=f"(d[48]),"=f"(d[49]),"=f"(d[50]),"=f"(d[51]),"=f"(d[52]),"=f"(d[53]),"=f"(d[54]),"=f"(d[55]),"=f"(d[56]),"=f"(d[57]),"=f"(d[58]),"=f"(d[59]),"=f"(d[60]),"=f"(d[61]),"=f"(d[62]),"=f"(d[63])
   :"r"(da),"r"(db):"memory");
}

__device__ __forceinline__ void wr_n152(float* d, uint32_t a0, uint32_t a1, uint32_t a2, uint64_t db) {
  asm volatile("{.reg .pred p; setp.eq.b32 p,0,0;\n"
   "wgmma.mma_async.sync.aligned.m64n152k16.f32.bf16.bf16 {%0,%1,%2,%3,%4,%5,%6,%7,%8,%9,%10,%11,%12,%13,%14,%15,%16,%17,%18,%19,%20,%21,%22,%23,%24,%25,%26,%27,%28,%29,%30,%31,%32,%33,%34,%35,%36,%37,%38,%39,%40,%41,%42,%43,%44,%45,%46,%47,%48,%49,%50,%51,%52,%53,%54,%55,%56,%57,%58,%59,%60,%61,%62,%63,%64,%65,%66,%67,%68,%69,%70,%71,%72,%73,%74,%75},{%76,%77,%78,%78},%79,p,1,1,0;}"
   :"+f"(d[0]),"+f"(d[1]),"+f"(d[2]),"+f"(d[3]),"+f"(d[4]),"+f"(d[5]),"+f"(d[6]),"+f"(d[7]),"+f"(d[8]),"+f"(d[9]),"+f"(d[10]),"+f"(d[11]),"+f"(d[12]),"+f"(d[13]),"+f"(d[14]),"+f"(d[15]),"+f"(d[16]),"+f"(d[17]),"+f"(d[18]),"+f"(d[19]),"+f"(d[20]),"+f"(d[21]),"+f"(d[22]),"+f"(d[23]),"+f"(d[24]),"+f"(d[25]),"+f"(d[26]),"+f"(d[27]),"+f"(d[28]),"+f"(d[29]),"+f"(d[30]),"+f"(d[31]),"+f"(d[32]),"+f"(d[33]),"+f"(d[34]),"+f"(d[35]),"+f"(d[36]),"+f"(d[37]),"+f"(d[38]),"+f"(d[39]),"+f"(d[40]),"+f"(d[41]),"+f"(d[42]),"+f"(d[43]),"+f"(d[44]),"+f"(d[45]),"+f"(d[46]),"+f"(d[47]),"+f"(d[48]),"+f"(d[49]),"+f"(d[50]),"+f"(d[51]),"+f"(d[52]),"+f"(d[53]),"+f"(d[54]),"+f"(d[55]),"+f"(d[56]),"+f"(d[57]),"+f"(d[58]),"+f"(d[59]),"+f"(d[60]),"+f"(d[61]),"+f"(d[62]),"+f"(d[63]),"+f"(d[64]),"+f"(d[65]),"+f"(d[66]),"+f"(d[67]),"+f"(d[68]),"+f"(d[69]),"+f"(d[70]),"+f"(d[71]),"+f"(d[72]),"+f"(d[73]),"+f"(d[74]),"+f"(d[75])
   :"r"(a0),"r"(a1),"r"(a2),"l"(db));
}
__device__ __forceinline__ void wr_n144(float* d, uint32_t a0, uint32_t a1, uint32_t a2, uint64_t db) {
  asm volatile("{.reg .pred p; setp.eq.b32 p,0,0;\n"
   "wgmma.mma_async.sync.aligned.m64n144k16.f32.bf16.bf16 {%0,%1,%2,%3,%4,%5,%6,%7,%8,%9,%10,%11,%12,%13,%14,%15,%16,%17,%18,%19,%20,%21,%22,%23,%24,%25,%26,%27,%28,%29,%30,%31,%32,%33,%34,%35,%36,%37,%38,%39,%40,%41,%42,%43,%44,%45,%46,%47,%48,%49,%50,%51,%52,%53,%54,%55,%56,%57,%58,%59,%60,%61,%62,%63,%64,%65,%66,%67,%68,%69,%70,%71},{%72,%73,%74,%74},%75,p,1,1,0;}"
   :"+f"(d[0]),"+f"(d[1]),"+f"(d[2]),"+f"(d[3]),"+f"(d[4]),"+f"(d[5]),"+f"(d[6]),"+f"(d[7]),"+f"(d[8]),"+f"(d[9]),"+f"(d[10]),"+f"(d[11]),"+f"(d[12]),"+f"(d[13]),"+f"(d[14]),"+f"(d[15]),"+f"(d[16]),"+f"(d[17]),"+f"(d[18]),"+f"(d[19]),"+f"(d[20]),"+f"(d[21]),"+f"(d[22]),"+f"(d[23]),"+f"(d[24]),"+f"(d[25]),"+f"(d[26]),"+f"(d[27]),"+f"(d[28]),"+f"(d[29]),"+f"(d[30]),"+f"(d[31]),"+f"(d[32]),"+f"(d[33]),"+f"(d[34]),"+f"(d[35]),"+f"(d[36]),"+f"(d[37]),"+f"(d[38]),"+f"(d[39]),"+f"(d[40]),"+f"(d[41]),"+f"(d[42]),"+f"(d[43]),"+f"(d[44]),"+f"(d[45]),"+f"(d[46]),"+f"(d[47]),"+f"(d[48]),"+f"(d[49]),"+f"(d[50]),"+f"(d[51]),"+f"(d[52]),"+f"(d[53]),"+f"(d[54]),"+f"(d[55]),"+f"(d[56]),"+f"(d[57]),"+f"(d[58]),"+f"(d[59]),"+f"(d[60]),"+f"(d[61]),"+f"(d[62]),"+f"(d[63]),"+f"(d[64]),"+f"(d[65]),"+f"(d[66]),"+f"(d[67]),"+f"(d[68]),"+f"(d[69]),"+f"(d[70]),"+f"(d[71])
   :"r"(a0),"r"(a1),"r"(a2),"l"(db));
}

__device__ __forceinline__ void wg_n72(float* d, uint64_t da, uint64_t db, int sd) {
  asm volatile("{.reg .pred p; setp.ne.b32 p,%38,0;\n"
   "wgmma.mma_async.sync.aligned.m64n72k16.f32.bf16.bf16 {%0,%1,%2,%3,%4,%5,%6,%7,%8,%9,%10,%11,%12,%13,%14,%15,%16,%17,%18,%19,%20,%21,%22,%23,%24,%25,%26,%27,%28,%29,%30,%31,%32,%33,%34,%35},%36,%37,p,1,1,1,0;}"
   :"+f"(d[0]),"+f"(d[1]),"+f"(d[2]),"+f"(d[3]),"+f"(d[4]),"+f"(d[5]),"+f"(d[6]),"+f"(d[7]),"+f"(d[8]),"+f"(d[9]),"+f"(d[10]),"+f"(d[11]),"+f"(d[12]),"+f"(d[13]),"+f"(d[14]),"+f"(d[15]),"+f"(d[16]),"+f"(d[17]),"+f"(d[18]),"+f"(d[19]),"+f"(d[20]),"+f"(d[21]),"+f"(d[22]),"+f"(d[23]),"+f"(d[24]),"+f"(d[25]),"+f"(d[26]),"+f"(d[27]),"+f"(d[28]),"+f"(d[29]),"+f"(d[30]),"+f"(d[31]),"+f"(d[32]),"+f"(d[33]),"+f"(d[34]),"+f"(d[35])
   :"l"(da),"l"(db),"r"(sd));
}
__device__ __forceinline__ void wg_n144(float* d, uint64_t da, uint64_t db, int sd) {
  asm volatile("{.reg .pred p; setp.ne.b32 p,%74,0;\n"
   "wgmma.mma_async.sync.aligned.m64n144k16.f32.bf16.bf16 {%0,%1,%2,%3,%4,%5,%6,%7,%8,%9,%10,%11,%12,%13,%14,%15,%16,%17,%18,%19,%20,%21,%22,%23,%24,%25,%26,%27,%28,%29,%30,%31,%32,%33,%34,%35,%36,%37,%38,%39,%40,%41,%42,%43,%44,%45,%46,%47,%48,%49,%50,%51,%52,%53,%54,%55,%56,%57,%58,%59,%60,%61,%62,%63,%64,%65,%66,%67,%68,%69,%70,%71},%72,%73,p,1,1,1,0;}"
   :"+f"(d[0]),"+f"(d[1]),"+f"(d[2]),"+f"(d[3]),"+f"(d[4]),"+f"(d[5]),"+f"(d[6]),"+f"(d[7]),"+f"(d[8]),"+f"(d[9]),"+f"(d[10]),"+f"(d[11]),"+f"(d[12]),"+f"(d[13]),"+f"(d[14]),"+f"(d[15]),"+f"(d[16]),"+f"(d[17]),"+f"(d[18]),"+f"(d[19]),"+f"(d[20]),"+f"(d[21]),"+f"(d[22]),"+f"(d[23]),"+f"(d[24]),"+f"(d[25]),"+f"(d[26]),"+f"(d[27]),"+f"(d[28]),"+f"(d[29]),"+f"(d[30]),"+f"(d[31]),"+f"(d[32]),"+f"(d[33]),"+f"(d[34]),"+f"(d[35]),"+f"(d[36]),"+f"(d[37]),"+f"(d[38]),"+f"(d[39]),"+f"(d[40]),"+f"(d[41]),"+f"(d[42]),"+f"(d[43]),"+f"(d[44]),"+f"(d[45]),"+f"(d[46]),"+f"(d[47]),"+f"(d[48]),"+f"(d[49]),"+f"(d[50]),"+f"(d[51]),"+f"(d[52]),"+f"(d[53]),"+f"(d[54]),"+f"(d[55]),"+f"(d[56]),"+f"(d[57]),"+f"(d[58]),"+f"(d[59]),"+f"(d[60]),"+f"(d[61]),"+f"(d[62]),"+f"(d[63]),"+f"(d[64]),"+f"(d[65]),"+f"(d[66]),"+f"(d[67]),"+f"(d[68]),"+f"(d[69]),"+f"(d[70]),"+f"(d[71])
   :"l"(da),"l"(db),"r"(sd));
}
__device__ __forceinline__ void wg_n152(float* d, uint64_t da, uint64_t db, int sd) {
  asm volatile("{.reg .pred p; setp.ne.b32 p,%78,0;\n"
   "wgmma.mma_async.sync.aligned.m64n152k16.f32.bf16.bf16 {%0,%1,%2,%3,%4,%5,%6,%7,%8,%9,%10,%11,%12,%13,%14,%15,%16,%17,%18,%19,%20,%21,%22,%23,%24,%25,%26,%27,%28,%29,%30,%31,%32,%33,%34,%35,%36,%37,%38,%39,%40,%41,%42,%43,%44,%45,%46,%47,%48,%49,%50,%51,%52,%53,%54,%55,%56,%57,%58,%59,%60,%61,%62,%63,%64,%65,%66,%67,%68,%69,%70,%71,%72,%73,%74,%75},%76,%77,p,1,1,1,0;}"
   :"+f"(d[0]),"+f"(d[1]),"+f"(d[2]),"+f"(d[3]),"+f"(d[4]),"+f"(d[5]),"+f"(d[6]),"+f"(d[7]),"+f"(d[8]),"+f"(d[9]),"+f"(d[10]),"+f"(d[11]),"+f"(d[12]),"+f"(d[13]),"+f"(d[14]),"+f"(d[15]),"+f"(d[16]),"+f"(d[17]),"+f"(d[18]),"+f"(d[19]),"+f"(d[20]),"+f"(d[21]),"+f"(d[22]),"+f"(d[23]),"+f"(d[24]),"+f"(d[25]),"+f"(d[26]),"+f"(d[27]),"+f"(d[28]),"+f"(d[29]),"+f"(d[30]),"+f"(d[31]),"+f"(d[32]),"+f"(d[33]),"+f"(d[34]),"+f"(d[35]),"+f"(d[36]),"+f"(d[37]),"+f"(d[38]),"+f"(d[39]),"+f"(d[40]),"+f"(d[41]),"+f"(d[42]),"+f"(d[43]),"+f"(d[44]),"+f"(d[45]),"+f"(d[46]),"+f"(d[47]),"+f"(d[48]),"+f"(d[49]),"+f"(d[50]),"+f"(d[51]),"+f"(d[52]),"+f"(d[53]),"+f"(d[54]),"+f"(d[55]),"+f"(d[56]),"+f"(d[57]),"+f"(d[58]),"+f"(d[59]),"+f"(d[60]),"+f"(d[61]),"+f"(d[62]),"+f"(d[63]),"+f"(d[64]),"+f"(d[65]),"+f"(d[66]),"+f"(d[67]),"+f"(d[68]),"+f"(d[69]),"+f"(d[70]),"+f"(d[71]),"+f"(d[72]),"+f"(d[73]),"+f"(d[74]),"+f"(d[75])
   :"l"(da),"l"(db),"r"(sd));
}

template <int N> DEVI void fence_regs(float* d) {
#pragma unroll
  for (int i = 0; i < N; i++) asm volatile("" : "+f"(d[i])::"memory");
}

struct KvRegs { uint32_t u[8][2]; };
struct KvAddr { uint32_t k[11], v, t; };
DEVI void kv_addr(KvAddr& ad, int lane) {
  const int a = lane >> 1;
  const uint32_t hf = (lane & 1) * 8;
#pragma unroll
  for (int i = 0; i < 11; i++) {
    const int row = i < 3 ? (5 + i) * 17 + a : (i - 3) * 17 + a + 1;
    ad.k[i] = pin(row * 64 + (((row >> 1) & 3) << 4) + hf);
  }
  ad.v = pin(KIN + a * 64 + (((a >> 1) & 3) << 4) + hf);
  ad.t = pin(KIN + VIN + hf * 4);
}
DEVI void kv_load(uint32_t buf, const CUtensorMap* tmK, const CUtensorMap* tmV, const __nv_bfloat16* shp, int ch, int rc, uint32_t bar) {
  tma3d(buf, tmK, ch, rc * 16 - 1, 0, bar);
  tma3d(buf + KIN, tmV, ch, rc * 16, 0, bar);
  bulk_load(buf + KIN + VIN, shp + ch * 4, 256, bar);
}
DEVI void kv_compute(KvRegs& o, const KvAddr& ad, uint32_t buf, int col) {
  uint2 kr[11], vr[8];
#pragma unroll
  for (int i = 0; i < 11; i++)
    asm volatile("ld.shared.v2.u32 {%0,%1},[%2];" : "=r"(kr[i].x), "=r"(kr[i].y) : "r"(buf + (ad.k[i] ^ (col << 4))) : "memory");
  const uint4 w0 = lds128(buf + ad.t + col * 64), w1 = lds128(buf + ad.t + col * 64 + 16);
#pragma unroll
  for (int i = 0; i < 8; i++)
    asm volatile("ld.shared.v2.u32 {%0,%1},[%2];" : "=r"(vr[i].x), "=r"(vr[i].y) : "r"(buf + (ad.v ^ (col << 4)) + i * 1024) : "memory");
  const uint32_t t0 = __byte_perm(w0.x, w0.z, 0x5410), t1 = __byte_perm(w0.x, w0.z, 0x7632), t2 = __byte_perm(w0.y, w0.w, 0x5410),
                 t3 = __byte_perm(w0.y, w0.w, 0x7632), s0 = __byte_perm(w1.x, w1.z, 0x5410), s1 = __byte_perm(w1.x, w1.z, 0x7632),
                 s2 = __byte_perm(w1.y, w1.w, 0x5410), s3 = __byte_perm(w1.y, w1.w, 0x7632);
#pragma unroll
  for (int i = 0; i < 8; i++) {
    o.u[i][0] = hmul2(hfma2(kr[i + 3].x, t0, hfma2(kr[i + 2].x, t1, hfma2(kr[i + 1].x, t2, hmul2(kr[i].x, t3)))), vr[i].x);
    o.u[i][1] = hmul2(hfma2(kr[i + 3].y, s0, hfma2(kr[i + 2].y, s1, hfma2(kr[i + 1].y, s2, hmul2(kr[i].y, s3)))), vr[i].y);
  }
}
DEVI uint4 kv_pack(const KvRegs& o, int ch) {
  const uint32_t sel = (ch & 1) ? 0x7632 : 0x5410;
  const int cp = ch >> 1;
  return make_uint4(__byte_perm(o.u[7][cp], o.u[6][cp], sel), __byte_perm(o.u[5][cp], o.u[4][cp], sel),
                    __byte_perm(o.u[3][cp], o.u[2][cp], sel), __byte_perm(o.u[1][cp], o.u[0][cp], sel));
}
DEVI void kv_store(const KvRegs& o, int ch8, int rc, int lane) {
  uint4* dst = (uint4*)g_U + (size_t)(ch8 + (lane & 1) * 4) * 256 + (255 - rc * 16 - (lane >> 1));
#pragma unroll
  for (int ch = 0; ch < 4; ch++) __stcg(dst + ch * 256, kv_pack(o, ch));
}
DEVI void kv_publish(int lane) {
  asm volatile("fence.acq_rel.gpu;" ::: "memory");
  __syncwarp();
  if (lane == 0) asm volatile("red.relaxed.gpu.global.add.u32 [%0],%1;" ::"l"(&g_ucnt), "r"(1u) : "memory");
}

template <int NT_> struct HRegs { static constexpr int K = (280 + NT_ - 1) / NT_; uint4 A[K], B[K]; uint32_t d; };
template <int NT_>
DEVI void conv_load_h(HRegs<NT_>& r, const __nv_bfloat16* h, const __nv_bfloat16* dp, int tid, bool act = true) {
  r.d = 0;
  if (act) r.d = *(const unsigned short*)dp;
#pragma unroll
  for (int k = 0; k < HRegs<NT_>::K; k++) r.A[k] = r.B[k] = make_uint4(0, 0, 0, 0);
  if (act) {
#pragma unroll
    for (int k = 0; k < HRegs<NT_>::K; k++) {
      const int idx = min(tid + NT_ * k, 279), m = (idx * 1873) >> 16, z = idx - 3 * m - 4;
      const uint4* p = (const uint4*)h + z;
      if (k > 0 || z >= 0) r.A[k] = __ldg(p);
      if (k > 0 || z >= -1) r.B[k] = __ldg(p + 1);
    }
  }
}
template <int NT_>
DEVI void conv_expand_h(const HRegs<NT_>& r, uint32_t hs, int tid) {
#pragma unroll
  for (int k = 0; k < HRegs<NT_>::K; k++) {
    const int idx = tid + NT_ * k, m = (idx * 1873) >> 16;
    const uint32_t a = hs + idx * 16 + (m >> 1) * (4480 - 2 * HCP);
    const uint4 A = r.A[k];
    uint4 B = r.B[k];
    if (k == 0 && tid == 3) B.x = __byte_perm(pack2(bflo(B.x) + bflo(r.d), 0.f), B.x, 0x7610);
    if (idx < 280) {
      sts128(a, A.y, A.z, A.w, B.x);
      sts128(a + 2 * HCP, A.z, A.w, B.x, B.y);
      sts128(a + 4 * HCP, A.w, B.x, B.y, B.z);
      sts128(a + 6 * HCP, B.x, B.y, B.z, B.w);
      if (A.x == 0xffffffffu) sts32(a, A.y);
    }
  }
}
struct URegs { uint4 v[2]; uint32_t n[2]; };
DEVI int u_chunk(int tid) { return (tid & 0x70) | ((tid & 3) << 2) | ((tid >> 2) & 3); }
DEVI void conv_load_u(URegs& r, const __nv_bfloat16* u, int tid) {
  const int z = u_chunk(tid);
  r.v[0] = __ldcg((const uint4*)u + z);
  r.v[1] = __ldcg((const uint4*)u + z + 128);
  r.n[0] = __ldcg((const uint32_t*)u + 4 * z + 4);
  r.n[1] = z == 127 ? 0u : __ldcg((const uint32_t*)u + 4 * z + 516);
}
DEVI void conv_load_u_smem(URegs& r, uint32_t u, int tid) {
  const uint32_t a = u + u_chunk(tid) * 16;
  r.v[0] = lds128(a);
  r.v[1] = lds128(a + 2048);
  r.n[0] = lds32(a + 16);
  r.n[1] = u_chunk(tid) == 127 ? 0u : lds32(a + 2064);
}
DEVI void conv_build_u(const URegs& r, uint32_t us, int tid) {
  const int z = u_chunk(tid);
  const uint32_t a = us + (z & 3) * UAP + (z >> 2) * 32;
#pragma unroll
  for (int k = 0; k < 2; k++) {
    const uint4 v = r.v[k];
    sts128(a + k * 1024, __funnelshift_r(v.x, v.y, 16), __funnelshift_r(v.y, v.z, 16), __funnelshift_r(v.z, v.w, 16),
           __funnelshift_r(v.w, r.n[k], 16));
    sts128(a + k * 1024 + 16, v.x, v.y, v.z, v.w);
  }
  if (tid < 64) sts128(us + (tid >> 4) * UAP + 2048 + (tid & 15) * 16, 0, 0, 0, 0);
}
DEVI void conv_channel(uint32_t hs, uint32_t us, uint32_t ys, int barid, int w, int lane, uint32_t donebar) {
  static_assert(HCP == 560 && UAP == 2320, "conv_mma has the table pitches built in");
  float acc[64];
  conv_mma(acc, ((hs & 0x3FFFF) >> 4) | (1u << 16), ((us & 0x3FFFF) >> 4) | ((uint32_t)(UAP >> 4) << 16));
  if (donebar) {
    if (lane == 0) mbar_arrive_n(donebar, 2);
  } else {
    bar_sync(barid, 128);
  }
  const int t = lane & 3;
  const bool q = lane & 16, up = !q && t == 3, dn = q && t == 0;
  const int src = ((lane ^ 16) & 28) | ((q ? t + 3 : t + 1) & 3);
  float keep[16], recv[16];
#pragma unroll
  for (int j = 0; j < 16; j++) {
    const float e0 = j < 14 ? acc[4 * j] + acc[4 * j + 10] : acc[4 * j], e1 = j < 14 ? acc[4 * j + 1] + acc[4 * j + 11] : acc[4 * j + 1];
    keep[j] = q ? e1 : e0;
    recv[j] = __shfl_sync(~0u, q ? e0 : e1, src);
  }
  const uint32_t a = ys + (q ? 2048 + 32 : 0) + (63 - t) * 32 + ((lane >> 2) & 3) * 8 + w * 2;
#pragma unroll
  for (int j = 0; j < 16; j += 2) {
    float v0 = up ? recv[j + 1] : recv[j], v1 = up ? (j + 2 < 16 ? recv[j + 2] : 0.f) : recv[j + 1];
    v0 = dn ? recv[(j + 15) & 15] : v0;
    v1 = dn ? recv[j] : v1;
    v0 += (j == 0 && dn) ? 0.f : keep[j];
    const uint32_t p = pack2(v0, v1 + keep[j + 1]);
    sts16((j == 0 && dn) ? a - 2048 : a - j * 128, p);
    sts16(a - j * 128 - 128, p >> 16);
  }
}

constexpr int SMEM_SIDE = 4 * (18432 + 9728) + 1024;
__global__ void __launch_bounds__(512) side_kernel(const __grid_constant__ CUtensorMap tmK, const __grid_constant__ CUtensorMap tmV,
                                                   const __nv_bfloat16* __restrict__ shp, const __nv_bfloat16* __restrict__ hp,
                                                   const __nv_bfloat16* __restrict__ Dp, int mode, int unit0, int ch_base, int utarget) {
  extern __shared__ __align__(1024) uint8_t smraw[];
  const uint32_t sb = s2u(smraw);
  const uint32_t bar = sb + SMEM_SIDE - 1024;
  const int tid = threadIdx.x, lane = tid & 31, warp = uni(tid >> 5);
  const uint32_t t0 = clk32();
  if (mode & 1) {
    const int u = unit0 + blockIdx.x;
    if (tid == 0) {
      mbar_init(bar, 1);
      fence_async_smem();
      mbar_expect(bar, 2 * KVIN);
      kv_load(sb, &tmK, &tmV, shp, (u >> 3) * 32, (u & 7) * 2, bar);
      kv_load(sb + 18432, &tmK, &tmV, shp, (u >> 3) * 32, (u & 7) * 2 + 1, bar);
    }
    __syncthreads();
    if (warp < 8) {
      mbar_wait(bar, 0, t0);
      KvRegs o;
      KvAddr ad;
      kv_addr(ad, lane);
      kv_compute(o, ad, sb + (warp >> 2) * 18432, warp & 3);
      kv_store(o, (u >> 3) * 32 + (warp & 3) * 8, (u & 7) * 2 + (warp >> 2), lane);
      asm volatile("fence.acq_rel.gpu;" ::: "memory");
    }
    __syncthreads();
    if (warp == 0) kv_publish(lane);
  }
  if (!(mode & 2)) return;
  const int wg = warp >> 2, ch = ch_base + blockIdx.x * 4 + wg;
  const uint32_t hs = sb + wg * (18432 + 9728), us = hs + 18432;
  HRegs<128> hr;
  conv_load_h(hr, hp + (size_t)ch * 2048, Dp + ch, tid & 127);
  conv_expand_h(hr, hs, tid & 127);
  flag_wait(&g_ucnt, utarget, t0);
  URegs ur;
  conv_load_u(ur, g_U + (size_t)ch * 2048, tid & 127);
  conv_build_u(ur, us, tid & 127);
  fence_async_smem();
  bar_sync(1 + wg, 128);
  conv_channel(hs, us, hs, 1 + wg, warp & 3, lane, 0u);
  fence_async_smem();
  bar_sync(1 + wg, 128);
  if ((tid & 127) == 0) {
    bulk_store(g_Y + (size_t)ch * 2048, hs, 4096);
    bulk_commit();
    bulk_wait0();
    asm volatile("red.relaxed.gpu.global.add.u32 [%0],%1;" ::"l"(&g_ycnt[ch >> 6]), "r"(1u) : "memory");
  }
}

struct Ctx {
  uint32_t sb;
  uint32_t t0;
};
DEVI uint32_t barx(const Ctx& c, int i) { return c.sb + OFF_BAR + 8 * i; }
DEVI uint32_t xslot(const Ctx& c, int p) { return c.sb + OFF_X + p * XSLOT; }
DEVI void bwait(const Ctx& c, int i, uint32_t ph) { mbar_wait(barx(c, i), ph, c.t0); }
DEVI void cluster_wait() { asm volatile("barrier.cluster.wait.aligned;" ::: "memory"); }

DEVI int ord(int rank, int i) { return i == 0 ? rank : (i <= rank ? i - 1 : i); }

DEVI float2 row_stats(const uint32_t* f, int lane) {
  const uint32_t ones = 0x3f803f80u;
  float d[8];
  mma16816_z(d, f[0], ones, f[1], ones, f[0], f[1]);
  mma16816_z(d + 4, f[4], ones, f[5], ones, f[4], f[5]);
  mma16816(d, f[2], ones, f[3], ones, f[2], f[3]);
  mma16816(d + 4, f[6], ones, f[7], ones, f[6], f[7]);
  const bool odd = lane & 4;
  return make_float2(odd ? d[3] + d[7] : d[2] + d[6], odd ? d[1] + d[5] : d[0] + d[4]);
}
DEVI void stats_send(float2 v, uint32_t dst, uint32_t bar, int lane) {
  const int src = (lane & 28) | (lane >> 3);
  v.x = __shfl_sync(~0u, v.x, src);
  v.y = __shfl_sync(~0u, v.y, src);
  st_async2(mapa(dst, lane & 3), v.x, v.y, mapa(bar, lane & 3));
  st_async2(mapa(dst, (lane & 3) + 4), v.x, v.y, mapa(bar, (lane & 3) + 4));
}
DEVI float2 finish_stats(uint32_t a, int pitch) {
  float2 v[8];
#pragma unroll
  for (int p = 0; p < 8; p++) v[p] = lds64f(a + p * pitch);
  const float s = ((v[0].x + v[1].x) + (v[2].x + v[3].x)) + ((v[4].x + v[5].x) + (v[6].x + v[7].x));
  const float q = ((v[0].y + v[1].y) + (v[2].y + v[3].y)) + ((v[4].y + v[5].y) + (v[6].y + v[7].y));
  const float mean = s * (1.f / 512.f);
  const float var = fmaxf(q * (1.f / 512.f) - mean * mean, 0.f);
  float r;
  asm("rsqrt.approx.ftz.f32 %0,%1;" : "=f"(r) : "f"(var + 1e-5f));
  return make_float2(r, -mean);
}

DEVI void attention(const Ctx& c, uint32_t qa, uint32_t qh, uint32_t ka, uint32_t va, uint32_t oa, uint32_t ra, int lane, int layer,
                    bool first, bool kfree, int vbar, int cnt) {
  const int g = lane >> 2, t = lane & 3;
  uint32_t kf[10][2], vf[10][2], qf[5][4];
  const bool prev0 = 2 * t > g, prev1 = 2 * t + 1 > g;
  const uint32_t mprev = (prev0 ? 0xffffu : 0u) | (prev1 ? 0xffff0000u : 0u);
  const float sc2 = 0.25f * 1.4426950408889634f;
  float rq[9], rk[9][2];
#pragma unroll
  for (int j = 0; j < 9; j++) {
    rq[j] = __uint_as_float(lds32(ra + g * 4 + j * 32)) * sc2;
    rk[j][0] = __uint_as_float(lds32(ra + t * 8 - (prev0 ? 32 : 0) + j * 32));
    rk[j][1] = __uint_as_float(lds32(ra + t * 8 + 4 - (prev1 ? 32 : 0) + j * 32));
  }
  bwait(c, B_KQST, layer);
  if ((threadIdx.x & 127) < 32 && layer == 0) STAMP(80 + (threadIdx.x >> 7) * ((80 < 100) ? 76 : -5));
#pragma unroll
  for (int u = 0; u < 5; u++) { ldsm4(qf[u], (u < 4 ? qa : qh) + u * 512); ldsm4(&kf[2 * u][0], ka + u * 512); }
  bwait(c, B_VDONE, layer);
  if ((threadIdx.x & 127) < 32 && layer == 0) STAMP(81 + (threadIdx.x >> 7) * ((81 < 100) ? 76 : -5));
  float l[9][2], mx[9];
#pragma unroll
  for (int u = 0; u < 5; u++) {
    float s0[4], s1[4], s2[4];
    mma16816_z(s0, qf[u][0], qf[u][1], qf[u][2], qf[u][3], kf[2 * u][0], kf[2 * u][1]);
    mma16816_z(s1, qf[u][0], qf[u][1], qf[u][2], qf[u][3], kf[2 * u + 1][0], kf[2 * u + 1][1]);
    if (u == 0 && first) { s0[0] = -INFINITY; s0[1] = -INFINITY; }
    l[2 * u][0] = (prev0 ? s0[0] : s1[0]) * rk[2 * u][0];
    l[2 * u][1] = (prev1 ? s0[1] : s1[1]) * rk[2 * u][1];
    if (u < 4) {
      mma16816_z(s2, qf[u][0], qf[u][1], qf[u][2], qf[u][3], kf[2 * u + 2][0], kf[2 * u + 2][1]);
      l[2 * u + 1][0] = (prev0 ? s1[2] : s2[2]) * rk[2 * u + 1][0];
      l[2 * u + 1][1] = (prev1 ? s1[3] : s2[3]) * rk[2 * u + 1][1];
    }
  }
#pragma unroll
  for (int j = 0; j < 9; j++) mx[j] = fmaxf(l[j][0], l[j][1]);
#pragma unroll
  for (int j = 0; j < 9; j++) mx[j] = fmaxf(mx[j], __shfl_xor_sync(~0u, mx[j], 1));
#pragma unroll
  for (int j = 0; j < 9; j++) mx[j] = -rq[j] * fmaxf(mx[j], __shfl_xor_sync(~0u, mx[j], 2));
  const uint32_t ones = 0x3f803f80u;
  uint32_t pp[9];
  float rs[9][2];
#pragma unroll
  for (int j = 0; j < 9; j++) {
    const float e0 = ex2(fmaf(l[j][0], rq[j], mx[j])), e1 = ex2(fmaf(l[j][1], rq[j], mx[j]));
    float sm[4];
    asm volatile("mma.sync.aligned.m16n8k8.row.col.f32.bf16.bf16.f32 {%0,%1,%2,%3},{%4,%4},{%5},{%6,%6,%6,%6};"
                 : "=f"(sm[0]), "=f"(sm[1]), "=f"(sm[2]), "=f"(sm[3]) : "r"(ones), "r"(pack2(e0, e1)), "f"(0.f));
    pp[j] = pack2(e0 * rk[j][0], e1 * rk[j][1]);
    const float r = rcp(sm[0] * sm[1]);
    rs[j][0] = r * sm[1];
    rs[j][1] = r * sm[0];
  }
  if ((threadIdx.x & 127) < 32 && layer == 0) STAMP(82 + (threadIdx.x >> 7) * ((82 < 100) ? 76 : -5));
  bar_sync(vbar, 64);
#pragma unroll
  for (int u = 0; u < 5; u++) ldsm4t(&vf[2 * u][0], va + u * 512);
  if (kfree) bwait(c, B_KFREE, 0);
  if (layer) {
    reads_done();
    __syncwarp();
    if (lane == 0) mbar_arrive_n(barx(c, B_X2ST), cnt);
  }
  uint32_t o[10][2];
#pragma unroll
  for (int j = 0; j < 9; j++) {
    float d[4];
    if (j & 1) {
      asm volatile("mma.sync.aligned.m16n8k8.row.col.f32.bf16.bf16.f32 {%0,%1,%2,%3},{%4,%5},{%6},{%7,%7,%7,%7};"
                   : "=f"(d[0]), "=f"(d[1]), "=f"(d[2]), "=f"(d[3]) : "r"(vf[j][0]), "r"(vf[j][1]), "r"(pp[j] & mprev), "f"(0.f));
      asm volatile("mma.sync.aligned.m16n8k8.row.col.f32.bf16.bf16.f32 {%0,%1,%2,%3},{%4,%5},{%6},{%0,%1,%2,%3};"
                   : "+f"(d[0]), "+f"(d[1]), "+f"(d[2]), "+f"(d[3]) : "r"(vf[j + 1][0]), "r"(vf[j + 1][1]), "r"(pp[j] & ~mprev));
    } else {
      mma16816_z(d, vf[j][0], vf[j][1], vf[j + 1][0], vf[j + 1][1], pp[j] & mprev, pp[j] & ~mprev);
    }
    o[j][0] = pack2(d[0] * rs[j][0], d[1] * rs[j][1]);
    o[j][1] = pack2(d[2] * rs[j][0], d[3] * rs[j][1]);
    if (j & 1) stsm4t(oa + (j - 1) * 256, o[j - 1][0], o[j - 1][1], o[j][0], o[j][1]);
  }
  stsm2t(oa + 2048, o[8][0], o[8][1]);
  if ((threadIdx.x & 127) < 32 && layer == 0) STAMP(117 + (threadIdx.x >> 7) * ((117 < 100) ? 76 : -5));
  fence_async_smem();
  __syncwarp();
  if (lane == 0) mbar_arrive_n(barx(c, B_STAGED), cnt);
  if ((threadIdx.x & 127) < 32 && layer == 0) STAMP(118 + (threadIdx.x >> 7) * ((118 < 100) ? 76 : -5));
}

#define ST(i) do { if (w == 0) STAMP(wg * 20 + layer * 10 + (i)); } while (0)

__global__ void __cluster_dims__(8, 1, 1) __launch_bounds__(512, 1)
main_kernel(const __grid_constant__ CUtensorMap tmX72, const __grid_constant__ CUtensorMap tmX7,
            const __grid_constant__ CUtensorMap tmW, const __grid_constant__ CUtensorMap tmWo,
            const __grid_constant__ CUtensorMap tmWo3,
            const __grid_constant__ CUtensorMap tmY, const __grid_constant__ CUtensorMap tmK,
            const __grid_constant__ CUtensorMap tmV, __nv_bfloat16* __restrict__ outp,
            const __nv_bfloat16* __restrict__ wqkvp, const __nv_bfloat16* __restrict__ wop,
            const __nv_bfloat16* __restrict__ kp, const __nv_bfloat16* __restrict__ vp,
            const __nv_bfloat16* __restrict__ shp, const __nv_bfloat16* __restrict__ hp,
            const __nv_bfloat16* __restrict__ Dp, int do_conv) {
  extern __shared__ __align__(1024) uint8_t smraw[];
  Ctx c;
  c.sb = s2u(smraw);
  c.t0 = clk32();
  asm volatile("griddepcontrol.launch_dependents;" ::: "memory");
  const int lane = threadIdx.x & 31;
  const int warp = uni(threadIdx.x >> 5);
  const int w = warp & 3, wg = warp >> 2;
  const int rank = blockIdx.x & 7, tile = blockIdx.x >> 3;
  const int ciA = 136 * tile;

  const int ciB = ciA + 72, ciH = ciA - 8;
  const int xH = (ciH >= 1024 ? 512 : 0) + rank * 64, yH = (ciH >= 1024 ? ciH - 1024 : ciH) + 1;
  const int xA = (ciA >> 10) * 512 + rank * 64, yA = ciA & 1023;
  const int xB = (ciB >> 10) * 512 + rank * 64, yB = ciB & 1023;
  const uint32_t own = xslot(c, rank);
  if (elect()) {
    const int cnt = warp < 12 ? 1 : (warp == 12 ? 8 : 12);
    if (warp == 5) {
      const uint32_t xb = barx(c, B_XOWN);
      mbar_init(xb, 1);
      fence_async_smem();
      tma2d(own, &tmX72, xA, yA, xb);
      tma2d(own + 9216, &tmX72, xB, yB, xb);
      tma2d(own + 145 * 128, &tmX7, xH, yH, xb);
      STAMP(73);
    } else if (warp == 0) {
#pragma unroll
      for (int i = 0; i < 3; i++) mbar_init(barx(c, i), 1);
      fence_async_smem();
#pragma unroll
      for (int s = 0; s < 3; s++) tma2d(c.sb + OFF_RING + s * RSLOT, &tmW, (s == 0 ? 512 : (s == 1 ? 0 : 1024)) + rank * 64, rank * 64, barx(c, B_FULL + s));
    } else {
      __nanosleep(100);
    }
#pragma unroll
    for (int i = 0; i < 7; i++)
      if ((i > 0 || warp != 5) && (i > 2 || warp != 0)) mbar_init(barx(c, warp * 7 + i), cnt);
    if (warp == 0) {
      fence_async_smem();
#pragma unroll
      for (int s = 3; s < NRING; s++)
        tma2d(c.sb + OFF_RING + s * RSLOT, &tmW, (s == 3 ? 512 : (s == 4 ? 0 : 1024)) + rank * 64, (rank == 0) * 64, barx(c, B_FULL + s));
    }
    asm volatile("fence.mbarrier_init.release.cluster;" ::: "memory");
    fence_async_smem();
  }
  if (warp == 1 || warp == 2) {
    const uint32_t o = 0x3f803f80u;
    const int i = threadIdx.x - 32;
    sts128(xslot(c, i >> 3) + 144 * 128 + (i & 7) * 16, o, o, o, o);
    fence_async_smem();
  }
  __syncwarp();
  asm volatile("barrier.cluster.arrive.relaxed.aligned;" ::: "memory");
  __syncthreads();
  if (warp == 0) STAMP(71);

  const int ch0 = tile * 32 + rank * 4;
  const uint32_t mtab = c.sb + OFF_STQ + (rank < 3 ? 3 * 1216 : 0);

  if (warp >= 12) {
    asm volatile("setmaxnreg.dec.sync.aligned.u32 80;");
    {
      const int b = threadIdx.x - 384;
      if (b < B_MRQ) {
        uint32_t n = 8192;
        if (b >= 32 && b < 35) n = 9216;
        if (b == B_XOWN || b >= B_XFULL) n = 151 * 128;
        if (b == B_KIN || b == B_VIN) n = KVIN;
        if (b == B_URAW) n = 16384;
        if (b == B_STQ) n = 7 * 1216;
        if (b == B_STB) n = 8 * 1152;
        mbar_expect(barx(c, b), n);
      }
    }
    cluster_wait();
    if (warp == 12) {
      const bool el = elect();
      uint32_t ph = 0, slot = 0, fb = barx(c, B_FULL + NRING);
#define ISSUE(TM, X, Y, FB)                                                        \
      {                                                                            \
        bwait(c, B_EMPTY + slot, ph);                                              \
        if (el) tma2d(c.sb + OFF_RING + slot * RSLOT, TM, X, Y, FB);               \
        fb += 8;                                                                   \
        if (++slot == NRING) { slot = 0; ph ^= 1; }                                \
      }
#pragma unroll 1
      for (int layer = 0; layer < 2; layer++) {
#pragma unroll 1
        for (int i = layer ? 0 : 2; i < 4; i++) {
          const int y = ord(rank, i) * 64;
#pragma unroll 1
          for (int part = 0; part < 3; part++) ISSUE(&tmW, ((0x201 >> (4 * part)) & 3) * 512 + rank * 64, y, fb)
        }
#pragma unroll 1
        for (int part = 0; part < 3; part++) {
          const int x = ((0x201 >> (4 * part)) & 3) * 512 + rank * 64;
#pragma unroll 1
          for (int p = ord(rank, 4); p < 8; p += (p + 1 == rank ? 2 : 1)) ISSUE(&tmW, x, p * 64, fb)
        }
        if (layer) {
#pragma unroll 1
          for (int i = 0; i < 8; i++) {
            bwait(c, B_EMPTY + slot, ph);
            if (el) tma3d(c.sb + OFF_RING + slot * RSLOT, &tmWo3, rank * 64, (i >> 1) * 16, (i & 1) * 4, fb);
            fb += 8;
            if (++slot == NRING) { slot = 0; ph ^= 1; }
          }
        } else {
#pragma unroll 1
          for (int i = 0; i < 8; i++) ISSUE(&tmWo, rank * 64, ord(rank, (OSEQ1 >> (4 * i)) & 7) * 64, fb)
          flag_wait(&g_ycnt[rank], 64u, c.t0);
          STAMP(60);
#pragma unroll 1
          for (int i = 0; i < 4; i++) ISSUE(&tmY, ciA + (i >> 1) * 72, rank * 64 + (i & 1) * 32, barx(c, B_FULL + 32 + (i >> 1)))
        }
      }
      if (el && atomicAdd(&g_done, 1u) == gridDim.x - 1) {
        for (int i = 0; i < 8; i++) g_ycnt[i] = 0;
        g_ucnt = 0;
        g_done = 0;
      }
    } else if (warp == 13) {
      const int pp = ord(rank, lane & 7);
      const bool el = elect();
      const uint32_t xfb = barx(c, B_XFULL + pp);
      const uint16_t others = (uint16_t)(0xff ^ (1u << rank));
      if (lane == 0) {
        tma2d_mc(own, &tmX72, xA, yA, xfb, others);
        tma2d_mc(own + 9216, &tmX72, xB, yB, xfb, others);
        tma2d_mc(own + 145 * 128, &tmX7, xH, yH, xfb, others);
      }
#pragma unroll 1
      for (int ex = 0; ex < 3; ex++) {
        if (ex != 1) {
          bar_sync(6, 416);
          if (ex == 2) bwait(c, B_TD + 1, 1);
          if (lane >= 1 && lane < 8) {
            const uint32_t a = c.sb + OFF_STQ + rank * 1216;
            bulk_s2s(mapa(a, pp), a, 1216, mapa(barx(c, B_STQ), pp));
          }
          bwait(c, B_STQ, ex >> 1);
          if (lane == 0 && ex == 0) mbar_expect(barx(c, B_STQ), 7 * 1216);
          float2 fs[5];
#pragma unroll
          for (int i = 0; i < 5; i++) fs[i] = finish_stats(c.sb + OFF_STQ + min(lane + 32 * i, 151) * 8, 1216);
          __syncwarp();
#pragma unroll
          for (int i = 0; i < 5; i++) {
            const int r = lane + 32 * i;
            const uint32_t hi = pack2(fs[i].y, fs[i].y), lo = pack2(fs[i].y - bflo(hi), fs[i].y - bflo(hi));
            if (r < 152) {
              sts128(mtab + r * 16, hi, lo, 0, 0);
              sts32(mtab + 2432 + (r < 144 ? r + 8 : r - 144) * 4, __float_as_uint(fs[i].x));
            }
          }
          fence_async_smem();
          __syncwarp();
          if (lane == 0) mbar_arrive(barx(c, B_MRQ));
          if (ex == 0 && do_conv) {
#pragma unroll
            for (int i = 0; i < 4; i++) asm volatile("prefetch.global.L2 [%0];" ::"l"(hp + (size_t)(ch0 + i) * 2048 + lane * 64));
            if (lane == 0) asm volatile("prefetch.global.L2 [%0];" ::"l"(Dp + ch0));
          }
        }
        uint8_t* gb = (ex == 1 ? g_exX : g_exO) + (size_t)tile * 8 * XSLOT + 256;
        if (ex == 0) {
          bwait(c, B_VDONE, 0);
          if (lane >= 1 && lane < 8) mbar_expect(xfb, XSLOT - 256);
        }
        if (ex == 2 && lane < 6) mbar_expect(barx(c, B_FULL + lane), ((lane & 1) == (rank >> 2) ? 3 : 4) * 4608);
        __syncwarp();
        uint8_t* gm = gb + rank * XSLOT;
        const uint32_t xob = ex == 2 ? barx(c, B_FULL + (rank >> 2)) : barx(c, B_XFULL + rank), xos = ex == 2 ? 16 : 0;
        const uint32_t xfr = mapa(barx(c, B_XFREE), lane & 7), sp = ex ? SUBT : 4800;
        if (ex == 2) {
          bwait(c, B_X2ST, 1);
          if (lane < 8) mbar_arrive_remote(xfr);
        }
        bwait(c, ex == 1 ? B_X2ST : B_STAGED, 0);
        STAMP(62 + ex * 3);
        if (el) {
#pragma unroll
          for (int k = 0; k < 4; k++) { bulk_store(gm + k * sp, own + 256 + k * sp, ex ? 4608 : 4800); bulk_commit(); }
        }
        if (ex == 2) bwait(c, B_XFREE, 1);
        if (ex == 1) {
          const uint32_t ts = clk32();
          while (clk32() - ts < rank * STAG1) {}
          __syncwarp();
        }
        if (ex > 0) {
          bulk_wait<3>();
          STAMP(63 + ex * 3);
          const uint32_t ts = clk32(), pace = ex == 2 ? STAG : 0;
          if (el) bulk_load_mc(own + 256, gm, 4608, xob, others);
          bulk_wait<2>();
          while (clk32() - ts < pace) {}
          if (el) bulk_load_mc(own + 256 + SUBT, gm + SUBT, 4608, xob + xos, others);
          bulk_wait<1>();
          while (clk32() - ts < 2 * pace) {}
          if (el) bulk_load_mc(own + 256 + 2 * SUBT, gm + 2 * SUBT, 4608, xob + 2 * xos, others);
          bulk_wait<0>();
          __syncwarp();
          if (ex == 2 && (lane >> 1) == 3) mbar_expect(barx(c, B_FULL + lane), ((lane & 1) == (rank >> 2) ? 3 : 4) * 4608);
          while (clk32() - ts < 3 * pace) {}
          if (el) bulk_load_mc(own + 256 + 3 * SUBT, gm + 3 * SUBT, 4608, xob + 3 * xos, others);
          STAMP(64 + ex * 3);
        } else {
          bulk_wait<0>();
        }
        if (ex == 0) {
          __syncwarp();
          if (lane < 8) mbar_arrive_remote(mapa(barx(c, B_OSTORED), lane));
          bwait(c, B_OSTORED, 0);
          const int step = do_conv ? (0x30214420u >> (4 * (lane & 7))) & 7 : 0;
#pragma unroll 1
          for (int st = 0; st < (do_conv ? 5 : 1); st++) {
            if (st > 0) bwait(c, B_CVD + st - 1, 0);
            if (lane >= 1 && lane < 8 && step == st) bulk_load(xslot(c, pp) + 256, gb + pp * XSLOT, XSLOT - 256, xfb);
          }
          if (lane >= 1 && lane < 8) {
            mbar_wait(xfb, 1, c.t0);
            mbar_expect(xfb, 4 * 4608);
          }
          __syncwarp();
        }
      }
    } else {
      const int at = threadIdx.x - 448;
      const uint32_t vb = xslot(c, ord(rank, 1));
      {
        const uint8_t* pw = (const uint8_t*)wqkvp + min(blockIdx.x * 104u + at, 12287u - 64u) * 128u;
        asm volatile("prefetch.global.L2 [%0];" ::"l"(pw));
        if (at < 40) asm volatile("prefetch.global.L2 [%0];" ::"l"(pw + 64 * 128));
      }
      { const uint32_t ts = c.t0; while (clk32() - ts < PFT) __nanosleep(50); }
      if (blockIdx.x < 64) asm volatile("prefetch.global.L2 [%0];" ::"l"((const uint8_t*)wop + blockIdx.x * 8192 + at * 128));
      if (do_conv) {
#pragma unroll
        for (int i = 0; i < 2; i++) {
          const size_t o = (size_t)(rank * 256 + (tile & 1) * 128 + i * 64 + at) * 512 + (tile >> 1) * 64;
          asm volatile("prefetch.global.L2 [%0];" ::"l"(kp + o));
          asm volatile("prefetch.global.L2 [%0];" ::"l"(vp + o));
        }
        KvAddr ad;
        kv_addr(ad, lane);
        if (at == 32) {
          bwait(c, B_TD, 0);
          kv_load(own, &tmK, &tmV, shp, tile * 32, rank * 2, barx(c, B_KIN));
        }
#pragma unroll 1
        for (int it = 0; it < 4; it++) {
          const int col = 2 * (it & 1) + (warp & 1);
          if (it == 1 && at == 32) {
            bwait(c, B_TD + 1, 0);
            kv_load(vb, &tmK, &tmV, shp, tile * 32, rank * 2 + 1, barx(c, B_VIN));
          }
          __syncwarp();
          bwait(c, B_KIN + (it >> 1), 0);
          if (warp == 14) STAMP(148 + it);
          KvRegs o;
          kv_compute(o, ad, it < 2 ? own : vb, col);
          if (warp == 14) STAMP(152 + it);
          const int dst = 2 * col + (lane & 1);
          const uint32_t da = mapa(c.sb + OFF_URAW + (255 - (rank * 2 + (it >> 1)) * 16 - (lane >> 1)) * 16, dst), db = mapa(barx(c, B_URAW), dst);
#pragma unroll
          for (int ch = 0; ch < 4; ch++) {
            const uint4 v = kv_pack(o, ch);
            st_async4(da + ch * 4096, v.x, v.y, v.z, v.w, db);
          }
        }
        bar_sync(5, 64);
        if (at == 0) mbar_arrive(barx(c, B_KFREE));
#pragma unroll 1
        for (int ch = 0; ch < 4; ch += (ch ? 1 : 2)) {
          HRegs<64> hr;
          const int a2 = pin(at);
          conv_load_h(hr, hp + (size_t)(ch0 + ch) * 2048, Dp + ch0 + ch, a2);
          bwait(c, ch == 0 ? B_HFREE : (ch == 2 ? B_VDONE : B_STAGED), 0);
          conv_expand_h(hr, xslot(c, ord(rank, (HSLOT >> (4 * ch)) & 7)), a2);
          fence_async_smem();
          __syncwarp();
          if (lane == 0) mbar_arrive_n(barx(c, B_TAB + ch), 4);
          if (warp == 14) STAMP(75 + (ch & 1));
        }
        if (at == 0) {
#pragma unroll 1
          for (int ch = 0; ch < 4; ch++) {
            bwait(c, B_YST + ch, 0);
            bulk_store(g_Y + (size_t)(ch0 + ch) * 2048, c.sb + OFF_URAW + ch * 4096, 4096);
            bulk_commit();
          }
          STAMP(74);
          bulk_wait0();
          asm volatile("red.relaxed.gpu.global.add.u32 [%0],%1;" ::"l"(&g_ycnt[ch0 >> 6]), "r"(4u) : "memory");
          STAMP(61);
        }
        __syncwarp();
      }
      if (warp == 14 && lane < 8) mbar_arrive_remote(mapa(barx(c, B_XFREE), lane));
    }
  } else {
    asm volatile("setmaxnreg.inc.sync.aligned.u32 144;");
    const int tid = w * 32 + lane;
    const int g = lane >> 2, t = lane & 3, mi = lane >> 3, r8 = lane & 7;
    const bool l0 = lane == 0;
    const uint32_t hoff = pin(w * SUBT + lane * 16);
    const uint32_t alo = (((c.sb & 0x3FFFF) + OFF_RING) >> 4) | (64u << 16);
    const uint32_t rsa = pin(own + 256 + (mi >> 1) * SUBT + (mi & 1) * 128 + r8 * 16 + warp * 256);
    uint32_t xr[10][2], yf[2][8];
    uint32_t csa0 = 0, csa1 = 0;
    const uint32_t xlo = (c.sb & 0x3FFFF) >> 4;
    const uint32_t sqd = pin(c.sb + OFF_STQ + rank * 1216 + warp * 64 + g * 8);
    uint32_t xra = pin(own + (72 * (wg & 1) + (mi >> 1) * 8 + r8) * 128 + (((2 * w + (mi & 1)) ^ r8) << 4)), xrs = 1024;
#pragma unroll 1
    for (int layer = 0; layer < 2; layer++) {
      const int sb0 = layer * 36;
      {
        float acc[76];
#pragma unroll
        for (int i = 0; i < 76; i++) acc[i] = 0.f;
        fence_regs<76>(acc);
        if (layer) bwait(c, B_STAGED, 1);
        if (layer == 0) {
      const uint32_t a1 = pin(own + (warp * 8 + r8) * 128 + ((mi ^ r8) << 4)), gs = warp < 7 ? 12 * 1024 : 0;
#pragma unroll 1
      for (int rep = 0; rep < 2; rep++) {
      uint32_t f[16];
      if (rep) bwait(c, B_XOWN, 0);
      if (warp == 8) STAMP(72);
      ldsm4(f, a1); ldsm4(f + 4, a1 ^ 64); ldsm4(f + 8, a1 + gs); ldsm4(f + 12, (a1 ^ 64) + gs);
      const float2 v0 = row_stats(f, lane), v1 = row_stats(f + 8, lane);
      if ((g >> 1) == t) {
        sts64f(sqd, v0.x, v0.y);
        if (warp < 7) sts64f(sqd + 768, v1.x, v1.y);
      }
      }
    }
        bwait(c, B_FULL + sb0 + wg, 0);
        if (layer == 0) bar_sync(4, 384);
        ST(0);
#define BATON 2
#define QKV_GEMM(WG0, WG, BLO, BHI, BSTEP, TAIL)                                                                     \
        {                                                                                                      \
          uint32_t da = alo + wg * (RSLOT >> 4), db = xlo + (BLO) + rank * (XSLOT >> 4);                       \
          uint32_t fb = barx(c, B_FULL + sb0 + 3 + wg), eb = 0, td = 0;                                        \
          int p = rank == 0, slot = 3 + wg;                                                                    \
          wg_fence();                                                                                          \
          WG0(acc, desc64(da, 0x40000040u), desc64(db, BHI), 1);                                               \
          WG(acc, desc64(da + 128, 0x40000040u), desc64(db + BSTEP, BHI), 1);                                  \
          WG(acc, desc64(da + 256, 0x40000040u), desc64(db + 2 * BSTEP, BHI), 1);                              \
          WG(acc, desc64(da + 384, 0x40000040u), desc64(db + 3 * BSTEP, BHI), 1);                              \
          wg_commit();                                                                                         \
          if (wg < 2) {                                                                 \
            _Pragma("unroll")                                                                                  \
            for (int j = 0; j < 8; j += 2) ldsm4t(&xr[j][0], xra + j * xrs);                                   \
            ldsm2t(&xr[8][0], xra + 8 * xrs);                                                                  \
          }                                                                                                    \
          fence_async_smem();                                                                                  \
          bar_arrive(6, 416);                                                                                  \
          if (layer == 0) cluster_wait();                                                                      \
          if (mbar_test(barx(c, B_XFULL + p), 0)) {                                                            \
            eb = barx(c, B_EMPTY + wg); td = barx(c, B_TD);                                                    \
          } else {                                                                                             \
            wg_wait<0>();                                                                                      \
            if (l0) { mbar_arrive_n(barx(c, B_EMPTY + wg), 3); mbar_arrive(barx(c, B_TD)); }                   \
            bwait(c, B_XFULL + p, 0);                                                                          \
          }                                                                                                    \
          mbar_wait(fb, 0, c.t0);                                                                              \
          _Pragma("unroll 1")                                                                                  \
          for (int i = 1; i < 4; i++) {                                                                        \
            da = alo + slot * (RSLOT >> 4);                                                                    \
            db = xlo + (BLO) + p * (XSLOT >> 4);                                                               \
            if (w == 0) STAMP(80 + ((fb - barx(c, B_FULL)) >> 3));                                             \
            wg_fence();                                                                                        \
            WG(acc, desc64(da, 0x40000040u), desc64(db, BHI), 1);                                              \
            wg_commit();                                                                                       \
            wg_wait<1>();                                                                                      \
            if (l0 && eb) mbar_arrive_n(eb, 3);                                                                \
            if (l0 && td) mbar_arrive(td);                                                                     \
            WG(acc, desc64(da + 128, 0x40000040u), desc64(db + BSTEP, BHI), 1);                                \
            WG(acc, desc64(da + 256, 0x40000040u), desc64(db + 2 * BSTEP, BHI), 1);                            \
            WG(acc, desc64(da + 384, 0x40000040u), desc64(db + 3 * BSTEP, BHI), 1);                            \
            wg_commit();                                                                                       \
            eb = barx(c, B_EMPTY + slot);                                                                      \
            td = (i & 1) ? barx(c, B_TD + i) : 0;                                                              \
            slot = 2 * wg + 3 - slot;                                                                          \
            fb += i < 3 ? 24 : 24 + 24 * wg;                                                                   \
            p += p + 1 == rank ? 2 : 1;                                                                        \
            if (i < 3 && !(mbar_test(barx(c, B_XFULL + p), 0) & mbar_test(fb, 0))) {                           \
              wg_wait<0>();                                                                                    \
              if (l0) { mbar_arrive_n(eb, 3); if (td) mbar_arrive(td); }                                       \
              eb = 0; td = 0;                                                                                  \
              bwait(c, B_XFULL + p, 0);                                                                        \
              mbar_wait(fb, 0, c.t0);                                                                          \
            }                                                                                                  \
          }                                                                                                    \
          uint32_t dav[4], dbv[4], ebv[4];                                                                     \
          _Pragma("unroll")                                                                                    \
          for (int i = 0; i < 4; i++) {                                                                        \
            const int sl = (0x543210543210ull >> (4 * (((0x240 >> (4 * wg)) & 7) + i))) & 7;                   \
            dav[i] = uni(pin(alo + sl * (RSLOT >> 4)));                                                        \
            dbv[i] = uni(pin(xlo + (BLO) + ord(rank, 4 + i) * (XSLOT >> 4)));                                  \
            ebv[i] = pin(barx(c, B_EMPTY + sl));                                                               \
          }                                                                                                    \
          if (wg > 0) {                                                 \
            wg_wait<0>();                                                                                      \
            if (l0) { mbar_arrive_n(eb, 3); mbar_arrive(td); }                                                 \
            eb = 0; td = 0;                                                                                    \
            mbar_wait(fb, 0, c.t0);                                                                            \
            bar_sync(9 + wg, 256);                                                                             \
          } else {                                                                                             \
            _Pragma("unroll 1")                                                                                \
            for (int q = 7; q >= p; q--) if (q != rank) bwait(c, B_XFULL + q, 0);                              \
            mbar_wait(fb, 0, c.t0);                                                                            \
          }                                                                                                    \
          _Pragma("unroll")                                                                                    \
          for (int i = 0; i < 4; i++) {                                                                        \
            if (w == 0) STAMP(80 + ((fb - barx(c, B_FULL)) >> 3) + i);                                         \
            wg_fence();                                                                                        \
            WG(acc, desc64(dav[i], 0x40000040u), desc64(dbv[i], BHI), 1);                                      \
            WG(acc, desc64(dav[i] + 128, 0x40000040u), desc64(dbv[i] + BSTEP, BHI), 1);                        \
            wg_commit();                                                                                       \
            const bool ok = i == 3 || mbar_test(fb + 8 * i + 8, 0);                                            \
            wg_wait<1>();                                                                                      \
            if (i == 0) {                                                                                      \
              if (l0 && eb) { mbar_arrive_n(eb, 3); mbar_arrive(td); }                                         \
            } else if (l0) {                                                                                   \
              mbar_arrive_n(ebv[i - 1], 3);                                                                    \
              if (i == 1) mbar_arrive(barx(c, B_HFREE));                                                       \
            }                                                                                                  \
            WG(acc, desc64(dav[i] + 256, 0x40000040u), desc64(dbv[i] + 2 * BSTEP, BHI), 1);                    \
            if (i == BATON && wg < 2) bar_arrive(10 + wg, 256);                                                \
            WG(acc, desc64(dav[i] + 384, 0x40000040u), desc64(dbv[i] + 3 * BSTEP, BHI), 1);                    \
            wg_commit();                                                                                       \
            if (!ok) mbar_wait(fb + 8 * i + 8, 0, c.t0);                                                       \
          }                                                                                                    \
          eb = ebv[3];                                                                                         \
          TAIL                                                                                                 \
          wg_wait<0>();                                                                                        \
          if (l0) {                                                                                            \
            mbar_arrive_n(eb, 3);                                                                              \
          }                                                                                                    \
        }
        if (layer == 0) {
          QKV_GEMM(wg_n152, wg_n152, (1u << 16), 0x40000040u, 2, bwait(c, B_MRQ, 0);)
        } else {
          QKV_GEMM(wg_n144, wg_n144, (16u | (8u << 16)), 16u, (SUBT >> 4),
                   bwait(c, B_MRQ, 1); wg_fence(); wr_n144(acc, csa0, csa1, 0u, desc64((mtab & 0x3FFFF) >> 4, 8u)); wg_commit();)
        }
        fence_regs<76>(acc);
        xra = own + hoff + 256 + (wg & 1) * 2304; xrs = 256;
        ST(1);
        if (layer == 0) {
          const float c0 = __shfl_sync(~0u, acc[72], lane & ~3), c1 = __shfl_sync(~0u, acc[74], lane & ~3);
          const uint32_t h = pack2(c0, c1);
          csa0 = t < 2 ? pack2(bflo(h), c0 - bflo(h)) : 0u;
          csa1 = t < 2 ? pack2(bfhi(h), c1 - bfhi(h)) : 0u;
          wg_fence();
          wr_n152(acc, csa0, csa1, 0u, desc64((mtab & 0x3FFFF) >> 4, 8u));
          wg_commit();
          wg_wait<0>();
          fence_regs<76>(acc);
        }
        if (wg == 2 && l0) mbar_arrive_n(barx(c, B_VDONE), 3);
        bwait(c, wg == 2 ? B_KQST : B_TD + 3, layer);
        const uint32_t sa = xslot(c, ord(rank, (0x632 >> (4 * wg)) & 7)) + hoff;
#pragma unroll
        for (int j = 0; j < 18; j += 2) {
          const float* a = &acc[j * 4];
          stsm4t(sa + 256 + j * 256, pack2(a[0], a[1]), pack2(a[2], a[3]), pack2(a[4], a[5]), pack2(a[6], a[7]));
        }
        stsm2t(sa, pack2(acc[72], acc[73]), pack2(acc[74], acc[75]));
        __syncwarp();
        if (wg == 2) { bar_arrive(w == 3 ? 7 : 1 + w, 64); bar_arrive(12 + w, 64); }
        else if (l0) mbar_arrive(barx(c, B_KQST));
      }
      const bool cv = layer == 0 && do_conv;
      ST(2);
      {
        if (wg < 2) {
          const uint32_t go = hoff + wg * 2304;
          const uint32_t qb = xslot(c, ord(rank, 3)) + go + 256;
          attention(c, qb + (mi == 1 ? 128 : (mi == 2 ? -128 : 0)), qb - ((mi + 1) >> 1) * 128, xslot(c, ord(rank, 2)) + go,
                    xslot(c, ord(rank, 6)) + go, xra, mtab + 2432 + 32 + wg * 288, lane, layer,
                    wg ? tile == 7 : (layer == 1 || tile == 0), cv, (wg ? 12 : 1) + (w == 3 && !wg ? 6 : w), 1 + (w & 1));
        }
        if (cv && wg != 1) {
          const int k = wg == 0;
          HRegs<128> hr;
          conv_load_h(hr, hp + (size_t)(ch0 + 1) * 2048, Dp + ch0 + 1, tid, wg == 2);
          bwait(c, k ? B_STAGED : B_KFREE, 0);
          bwait(c, B_URAW, 0);
          URegs u0, u1;
          conv_load_u_smem(u0, c.sb + OFF_URAW + k * 8192, tid);
          conv_load_u_smem(u1, c.sb + OFF_URAW + k * 8192 + 4096, tid);
          conv_build_u(u0, xslot(c, ord(rank, 1 + k)), tid);
          conv_build_u(u1, xslot(c, ord(rank, 1 + k)) + UCH, tid);
          if (wg == 2) conv_expand_h(hr, xslot(c, ord(rank, (HSLOT >> 4) & 7)), tid);
          fence_async_smem();
          __syncwarp();
          if (lane < 2) mbar_arrive_n(barx(c, B_TAB + 2 * k + lane), (wg == 2 && lane == 1) ? 3 : 1);
        }
      }
      ST(4);
      if (cv) {
        bwait(c, B_STAGED, 0);
#pragma unroll 1
        for (int ch = (0x102 >> (4 * wg)) & 3; ch < 4; ch += (wg == 2 ? 2 : 4)) {
          const uint32_t hs = xslot(c, ord(rank, (HSLOT >> (4 * ch)) & 7)), us = xslot(c, ord(rank, 1 + (ch >> 1))) + (ch & 1) * UCH;
          bwait(c, B_TAB + ch, 0);
          if (ch < 3) ST(3); else ST(9);
          conv_channel(hs, us, c.sb + OFF_URAW + ch * 4096, 0, w, lane, barx(c, B_CVD + ch));
          fence_async_smem();
          __syncwarp();
          if (l0) mbar_arrive_n(barx(c, B_YST + ch), 3);
        }
      }
      ST(5);
      {
        if (wg < 2) {
          float acc[36];
          const uint32_t sta = xra;
#pragma unroll
          for (int j = 0; j < 9; j++) {
            acc[j * 4 + 0] = bflo(xr[j][0]); acc[j * 4 + 1] = bfhi(xr[j][0]);
            acc[j * 4 + 2] = bflo(xr[j][1]); acc[j * 4 + 3] = bfhi(xr[j][1]);
          }
          fence_regs<36>(acc);
          const uint32_t blo = (((c.sb & 0x3FFFF) + 256 + wg * 2304) >> 4) | (8u << 16);
          const uint32_t bst = layer ? (XSLOT >> 4) : (SUBT >> 4);
          uint32_t dbv[8], xbv[8];
#pragma unroll
          for (int i = 0; i < 8; i++) {
            const int p = ord(rank, (OSEQ1 >> (4 * i)) & 7);
            dbv[i] = uni(pin(blo + (layer ? (i >> 1) * (SUBT >> 4) + (i & 1) * (XSLOT >> 2) : p * (XSLOT >> 4))));
            xbv[i] = uni(pin(layer ? barx(c, B_FULL + i) : barx(c, B_XFULL + p)));
          }
          const uint32_t fb = barx(c, B_FULL + sb0 + 24), rn = 1 + (w & 1);
          bwait(c, B_STAGED, 0);
          mbar_wait(fb, 0, c.t0);
          if (layer) bwait(c, B_FULL, 1);
          if (cv) bwait(c, B_YST + 3, 0);
#pragma unroll
          for (int i = 0; i < 8; i++) {
            const uint32_t da = alo + (i % NRING) * (RSLOT >> 4), db = dbv[i];
            if (warp == 0) STAMP(80 + sb0 + 24 + i);
            wg_fence();
            wg_n72(acc, desc64(da, 0x40000040u), desc64(db, 16u), 1);
            wg_n72(acc, desc64(da + 128, 0x40000040u), desc64(db + bst, 16u), 1);
            const bool ok = i == 7 || (mbar_test(xbv[(i + 1) & 7], 1) & mbar_test(fb + 8 * i + 8, 0));
            wg_commit();
            wg_wait<1>();
            if (l0 && i > 0) mbar_arrive_n(barx(c, B_EMPTY + (i - 1) % NRING), rn);
            wg_n72(acc, desc64(da + 256, 0x40000040u), desc64(db + 2 * bst, 16u), 1);
            wg_n72(acc, desc64(da + 384, 0x40000040u), desc64(db + 3 * bst, 16u), 1);
            wg_commit();
            if (!ok) {
              mbar_wait(xbv[(i + 1) & 7], 1, c.t0);
              mbar_wait(fb + 8 * i + 8, 0, c.t0);
            }
          }
          wg_wait<0>();
          fence_regs<36>(acc);
          if (l0) mbar_arrive_n(barx(c, B_EMPTY + 1), 1 + (w & 1));
          ST(6);
#pragma unroll
          for (int j = 0; j < 8; j += 2)
            stsm4t(sta + j * 256, pack2(acc[j * 4], acc[j * 4 + 1]), pack2(acc[j * 4 + 2], acc[j * 4 + 3]),
                   pack2(acc[j * 4 + 4], acc[j * 4 + 5]), pack2(acc[j * 4 + 6], acc[j * 4 + 7]));
          stsm2t(sta + 2048, pack2(acc[32], acc[33]), pack2(acc[34], acc[35]));
        } else if (layer == 0) {
          for (int i = 1; i < 8; i++) bwait(c, B_XFULL + ord(rank, i), 1);
        }
        const bool two = warp >= 6;
        const uint32_t sbd = sqd + (OFF_STB - OFF_STQ) - rank * (1216 - STBP);
        if (layer == 0) bwait(c, B_XFREE, 0);
        bar_sync(4, 384);
        uint32_t f[2][8];
        ldsm4(f[0], rsa); ldsm4(f[0] + 4, rsa + 2 * SUBT);
        ldsm4(f[1], rsa + 1536); ldsm4(f[1] + 4, rsa + 2 * SUBT + 1536);
        stats_send(row_stats(f[0], lane), sbd, barx(c, B_STB), lane);
        if (two) stats_send(row_stats(f[1], lane), sbd + 384, barx(c, B_STB), lane);
        if (layer == 0) {
          bwait(c, B_FULL + 32, 0);
          bwait(c, B_FULL + 33, 0);
          const uint32_t a = c.sb + OFF_RING + 2 * RSLOT + lane * 144;
          const uint32_t a0 = a + warp * 16 + (warp >= 9 ? 2 * RSLOT - 144 : 0), a1 = a + 2 * RSLOT + (two ? warp - 3 : 0) * 16;
          ldsm4t(yf[0], a0); ldsm4t(yf[0] + 4, a0 + RSLOT);
          ldsm4t(yf[1], a1); ldsm4t(yf[1] + 4, a1 + RSLOT);
          reads_done();
          __syncwarp();
          if (lane < 4) mbar_arrive(barx(c, B_EMPTY + 2 + lane));
        }
        float xu[2][16], yu[2][16];
#pragma unroll
        for (int k = 0; k < 2; k++) {
#pragma unroll
          for (int i = 0; i < 8; i++) {
            xu[k][2 * i] = bflo(f[k][i]); xu[k][2 * i + 1] = bfhi(f[k][i]);
            yu[k][2 * i] = bflo(yf[k][i]); yu[k][2 * i + 1] = bfhi(yf[k][i]);
          }
          fence_regs<16>(xu[k]);
          fence_regs<16>(yu[k]);
        }
        const uint32_t pa = c.sb + OFF_STB + t * STBP + warp * 64 + g * 8;
        bwait(c, B_STB, layer);
        ST(7);
        if (threadIdx.x == 0) mbar_expect(barx(c, B_STB), 8 * 1152);
        {
          float s[2], q[2];
#pragma unroll
          for (int k = 0; k < 2; k++) {
            const float2 p0 = lds64f(pa + k * 384), p1 = lds64f(pa + k * 384 + 4 * STBP);
            s[k] = p0.x + p1.x; q[k] = p0.y + p1.y;
          }
#pragma unroll
          for (int o = 1; o < 4; o <<= 1)
#pragma unroll
            for (int k = 0; k < 2; k++) { s[k] += __shfl_xor_sync(~0u, s[k], o); q[k] += __shfl_xor_sync(~0u, q[k], o); }
#pragma unroll
          for (int k = 0; k < 2; k++) {
            const float mean = s[k] * (1.f / 512.f);
            float r;
            asm("rsqrt.approx.ftz.f32 %0,%1;" : "=f"(r) : "f"(fmaxf(q[k] * (1.f / 512.f) - mean * mean, 0.f) + 1e-5f));
            const float mr = -mean * r;
            if (k == 0 || two) {
#pragma unroll
              for (int i = 0; i < 8; i++)
                f[k][i] = pack2(fmaf(yu[k][2 * i], fmaf(xu[k][2 * i], r, mr), xu[k][2 * i]),
                                fmaf(yu[k][2 * i + 1], fmaf(xu[k][2 * i + 1], r, mr), xu[k][2 * i + 1]));
              stsm4(rsa + k * 1536, f[k][0], f[k][1], f[k][2], f[k][3]);
              stsm4(rsa + k * 1536 + 2 * SUBT, f[k][4], f[k][5], f[k][6], f[k][7]);
            }
          }
        }
        if (layer == 0) {
          fence_async_smem();
          __syncwarp();
          if (l0) mbar_arrive(barx(c, B_X2ST));
          const float2 v0 = row_stats(f[0], lane), v1 = row_stats(f[1], lane);
          if ((g >> 1) == t) {
            sts64f(sqd, v0.x, v0.y);
            if (two) sts64f(sqd + 384, v1.x, v1.y);
          }
          __syncwarp();
          if (l0) mbar_arrive(barx(c, B_STAGED));
        }
      }
      ST(8);
    }
    __syncwarp();
    {
      uint4 v[4];
#pragma unroll
      for (int k = 0; k < 4; k++) v[k] = lds128(rsa + (k >> 1) * 1536 + (k & 1) * 2 * SUBT);
#pragma unroll
      for (int k = 0; k < 2; k++) {
        const int ci = ciA + (warp + k * 6) * 8 + r8;
        uint4* o = (uint4*)(outp + (size_t)(ci & 1023) * 1024 + (ci >> 10) * 512 + rank * 64 + mi * 8);
        if (k ? warp >= 6 : (warp > 0 || tile == 0)) { o[0] = v[2 * k]; o[4] = v[2 * k + 1]; }
      }
    }
    { const int layer = 1; ST(9); }
  }
}

typedef CUresult (*EncFn)(CUtensorMap*, CUtensorMapDataType, cuuint32_t, void*, const cuuint64_t*, const cuuint64_t*,
                          const cuuint32_t*, const cuuint32_t*, CUtensorMapInterleave, CUtensorMapSwizzle,
                          CUtensorMapL2promotion, CUtensorMapFloatOOBfill);

static void enc2d(EncFn fn, CUtensorMap* tm, const void* base, uint64_t w, uint64_t h, uint32_t bw, uint32_t bh, bool swz) {
  cuuint64_t gd[2] = {w, h};
  cuuint64_t gs[1] = {w * 2};
  cuuint32_t bd[2] = {bw, bh};
  cuuint32_t es[2] = {1, 1};
  fn(tm, CU_TENSOR_MAP_DATA_TYPE_BFLOAT16, 2, const_cast<void*>(base), gd, gs, bd, es, CU_TENSOR_MAP_INTERLEAVE_NONE,
     swz ? CU_TENSOR_MAP_SWIZZLE_128B : CU_TENSOR_MAP_SWIZZLE_NONE, CU_TENSOR_MAP_L2_PROMOTION_L2_128B,
     CU_TENSOR_MAP_FLOAT_OOB_FILL_NONE);
}

extern "C" void kernel_launch(void* const* d_in, const int* in_sizes, int n_in, void* d_out, int out_size) {
  const __nv_bfloat16* x = (const __nv_bfloat16*)d_in[0];
  const __nv_bfloat16* wqkv = (const __nv_bfloat16*)d_in[1];
  const __nv_bfloat16* wo = (const __nv_bfloat16*)d_in[2];
  const __nv_bfloat16* kp = (const __nv_bfloat16*)d_in[4];
  const __nv_bfloat16* vp = (const __nv_bfloat16*)d_in[5];
  const __nv_bfloat16* shp = (const __nv_bfloat16*)d_in[6];
  const __nv_bfloat16* hp = (const __nv_bfloat16*)d_in[7];
  const __nv_bfloat16* Dp = (const __nv_bfloat16*)d_in[8];

  static EncFn enc = nullptr;
  static void* ybase = nullptr;
  static int fused = 0;
  cudaStream_t st = cudaStreamPerThread;
  cudaLaunchConfig_t cfg = {};
  cfg.gridDim = dim3(NT * 8);
  cfg.blockDim = dim3(512);
  cfg.dynamicSmemBytes = SMEM_MAIN;
  cfg.stream = st;
  if (!enc) {
    void* fn = nullptr;
    cudaDriverEntryPointQueryResult qr;
    cudaGetDriverEntryPoint("cuTensorMapEncodeTiled", &fn, cudaEnableDefault, &qr);
    enc = (EncFn)fn;
    cudaGetSymbolAddress(&ybase, g_Y);
    cudaFuncSetAttribute(main_kernel, cudaFuncAttributeMaxDynamicSharedMemorySize, SMEM_MAIN);
    cudaFuncSetAttribute(side_kernel, cudaFuncAttributeMaxDynamicSharedMemorySize, SMEM_SIDE);
    int ncl = 0, nsm = 0, dev = 0;
    cudaGetDevice(&dev);
    cudaDeviceGetAttribute(&nsm, cudaDevAttrMultiProcessorCount, dev);
    cudaOccupancyMaxActiveClusters(&ncl, main_kernel, &cfg);
    fused = (ncl >= NT && nsm >= NT * 8 + 8) ? 1 : 0;
    (void)cudaGetLastError();
  }
  CUtensorMap tmX72, tmX7, tmW, tmWo, tmY;
  enc2d(enc, &tmX72, x, 1024, 1024, 64, 72, true);
  enc2d(enc, &tmX7, x, 1024, 1024, 64, 7, true);
  enc2d(enc, &tmW, wqkv, 1536, 512, 64, 64, true);
  enc2d(enc, &tmWo, wo, 512, 512, 64, 64, true);
  enc2d(enc, &tmY, ybase, 2048, 512, 72, 32, false);
  __nv_bfloat16* outp = (__nv_bfloat16*)d_out;

  CUtensorMap tmWo3;
  {
    cuuint64_t gd[3] = {512, 64, 8};
    cuuint64_t gs[2] = {1024, 65536};
    cuuint32_t bd[3] = {64, 16, 4};
    cuuint32_t es[3] = {1, 1, 1};
    enc(&tmWo3, CU_TENSOR_MAP_DATA_TYPE_BFLOAT16, 3, const_cast<__nv_bfloat16*>(wo), gd, gs, bd, es, CU_TENSOR_MAP_INTERLEAVE_NONE,
        CU_TENSOR_MAP_SWIZZLE_128B, CU_TENSOR_MAP_L2_PROMOTION_L2_128B, CU_TENSOR_MAP_FLOAT_OOB_FILL_NONE);
  }
  CUtensorMap tmK, tmV;
  for (int i = 0; i < 2; i++) {
    cuuint64_t gd[3] = {512, 256, 8};
    cuuint64_t gs[2] = {8192, 1024};
    cuuint32_t bd[3] = {32, (cuuint32_t)(i ? 16 : 17), 8};
    cuuint32_t es[3] = {1, 1, 1};
    enc(i ? &tmV : &tmK, CU_TENSOR_MAP_DATA_TYPE_BFLOAT16, 3, const_cast<__nv_bfloat16*>(i ? vp : kp), gd, gs, bd, es,
        CU_TENSOR_MAP_INTERLEAVE_NONE, CU_TENSOR_MAP_SWIZZLE_64B, CU_TENSOR_MAP_L2_PROMOTION_L2_128B, CU_TENSOR_MAP_FLOAT_OOB_FILL_NONE);
  }

  if (fused) {
    cudaLaunchKernelEx(&cfg, main_kernel, tmX72, tmX7, tmW, tmWo, tmWo3, tmY, tmK, tmV, outp, wqkv, wo, kp, vp, shp, hp, Dp, 1);
    cudaLaunchConfig_t c2 = {};
    c2.gridDim = dim3(8);
    c2.blockDim = dim3(512);
    c2.dynamicSmemBytes = SMEM_SIDE;
    c2.stream = st;
    cudaLaunchAttribute a2[1];
    a2[0].id = cudaLaunchAttributeProgrammaticStreamSerialization;
    a2[0].val.programmaticStreamSerializationAllowed = 1;
    c2.attrs = a2;
    c2.numAttrs = 1;
    cudaLaunchKernelEx(&c2, side_kernel, tmK, tmV, shp, hp, Dp, 3, 120, 480, 8);
  } else {
    side_kernel<<<128, 512, SMEM_SIDE, st>>>(tmK, tmV, shp, hp, Dp, 1, 0, 0, 0);
    side_kernel<<<128, 512, SMEM_SIDE, st>>>(tmK, tmV, shp, hp, Dp, 2, 0, 0, 0);
    cudaLaunchKernelEx(&cfg, main_kernel, tmX72, tmX7, tmW, tmWo, tmWo3, tmY, tmK, tmV, outp, wqkv, wo, kp, vp, shp, hp, Dp, 0);
  }
}
```

```cpp
#include <cuda_runtime.h>
#include <cuda_bf16.h>
#include <cuda.h>
#include <stdint.h>

#define DEVI __device__ __forceinline__


namespace {

constexpr int NT = 15;
constexpr int XSLOT = 19456;
constexpr int SUBT = 4864;
constexpr int RSLOT = 8192;
constexpr unsigned PFT = 2300;
constexpr int STAG1 = 300;
constexpr int STAG = 450;
constexpr int NRING = 6;
constexpr int OFF_X = 0;
constexpr int OFF_RING = 8 * XSLOT;
constexpr int OFF_STQ = OFF_RING + NRING * RSLOT;
constexpr int OFF_BAR = OFF_STQ + 8 * 1216;
constexpr int OFF_STB = OFF_BAR + 896;
constexpr int STBP = 1216;
constexpr int OFF_URAW = OFF_STB;
constexpr int SMEM_MAIN = OFF_URAW + 16384;
static_assert(SMEM_MAIN <= 232448, "smem");

constexpr int UAP = 2320;
constexpr int UCH = 4 * UAP;
constexpr int HCP = 560;
constexpr int KIN = 17 * 8 * 64, VIN = 16 * 8 * 64;
constexpr int KVIN = KIN + VIN + 256;

enum { B_FULL = 0, B_XOWN = 35, B_XFULL = 68, B_KIN = 76, B_VIN, B_URAW, B_STQ, B_STB, B_MRQ, B_KFREE,
       B_OSTORED = 84, B_XFREE, B_KQST, B_CVD,
       B_EMPTY = 91, B_STAGED = 97, B_VDONE, B_TD,
       B_HFREE = B_TD + 4, B_YST, B_TAB = B_YST + 4,
       B_COUNT = B_TAB + 4,
       B_X2ST = B_TD + 2 };
constexpr unsigned OSEQ1 = 0x23715460u;
constexpr unsigned HSLOT = 0x3754u;

}

__device__ __align__(1024) __nv_bfloat16 g_Y[512 * 2048];
__device__ __align__(1024) uint8_t g_exO[NT * 8 * XSLOT];
__device__ __align__(1024) uint8_t g_exX[NT * 8 * XSLOT];
__device__ __align__(1024) __nv_bfloat16 g_U[512 * 2048];
__device__ unsigned g_ycnt[8];
__device__ unsigned g_ucnt;
__device__ unsigned g_done;

DEVI uint32_t s2u(const void* p) { return (uint32_t)__cvta_generic_to_shared(p); }
DEVI void mbar_init(uint32_t b, int c) { asm volatile("mbarrier.init.shared::cta.b64 [%0], %1;" ::"r"(b), "r"(c) : "memory"); }
DEVI void mbar_expect(uint32_t b, uint32_t bytes) {
  asm volatile("mbarrier.arrive.expect_tx.shared::cta.b64 _, [%0], %1;" ::"r"(b), "r"(bytes) : "memory");
}
DEVI void mbar_arrive(uint32_t b) { asm volatile("mbarrier.arrive.shared::cta.b64 _, [%0];" ::"r"(b) : "memory"); }
DEVI void mbar_arrive_n(uint32_t b, int n) { asm volatile("mbarrier.arrive.shared::cta.b64 _, [%0], %1;" ::"r"(b), "r"(n) : "memory"); }
DEVI void mbar_arrive_remote(uint32_t b) {
  asm volatile("mbarrier.arrive.relaxed.cluster.shared::cluster.b64 _, [%0];" ::"r"(b) : "memory");
}
DEVI uint32_t clk32() { uint32_t t; asm volatile("mov.u32 %0,%%clock;" : "=r"(t)); return t; }
DEVI bool expired(uint32_t t0) { return clk32() - t0 > (1u << 28); }
DEVI void mbar_wait(uint32_t b, uint32_t ph, uint32_t t0) {
  uint32_t ok;
  do {
    asm volatile("{.reg .pred p; mbarrier.try_wait.parity.shared::cta.b64 p,[%1],%2; selp.u32 %0,1,0,p;}"
                 : "=r"(ok) : "r"(b), "r"(ph) : "memory");
  } while (!ok && !expired(t0));
}
DEVI bool mbar_test(uint32_t b, uint32_t ph) {
  uint32_t ok;
  asm volatile("{.reg .pred p; mbarrier.test_wait.parity.shared::cta.b64 p,[%1],%2; selp.u32 %0,1,0,p;}"
               : "=r"(ok) : "r"(b), "r"(ph) : "memory");
  return ok;
}
DEVI uint32_t mapa(uint32_t a, uint32_t r) {
  uint32_t o;
  asm("mapa.shared::cluster.u32 %0,%1,%2;" : "=r"(o) : "r"(a), "r"(r));
  return o;
}
DEVI void fence_async_smem() { asm volatile("fence.proxy.async.shared::cta;" ::: "memory"); }
DEVI void reads_done() { asm volatile("fence.acq_rel.cta;" ::: "memory"); }
DEVI void bar_sync(int id, int n) { __syncwarp(); asm volatile("bar.sync %0,%1;" ::"r"(id), "r"(n) : "memory"); }
DEVI void bar_arrive(int id, int n) { __syncwarp(); asm volatile("bar.arrive %0,%1;" ::"r"(id), "r"(n) : "memory"); }
DEVI void tma2d(uint32_t dst, const CUtensorMap* tm, int x, int y, uint32_t bar) {
  asm volatile("cp.async.bulk.tensor.2d.shared::cluster.global.mbarrier::complete_tx::bytes [%0],[%1,{%3,%4}],[%2];"
               ::"r"(dst), "l"(tm), "r"(bar), "r"(x), "r"(y) : "memory");
}
DEVI void tma3d(uint32_t dst, const CUtensorMap* tm, int x, int y, int z, uint32_t bar) {
  asm volatile("cp.async.bulk.tensor.3d.shared::cluster.global.mbarrier::complete_tx::bytes [%0],[%1,{%3,%4,%5}],[%2];"
               ::"r"(dst), "l"(tm), "r"(bar), "r"(x), "r"(y), "r"(z) : "memory");
}
DEVI void flag_wait(const unsigned* p, unsigned target, uint32_t t0) {
  unsigned v;
  while (true) {
    asm volatile("ld.relaxed.gpu.global.u32 %0,[%1];" : "=r"(v) : "l"(p) : "memory");
    if (v >= target || expired(t0)) break;
    __nanosleep(40);
  }
}
DEVI void tma2d_mc(uint32_t dst, const CUtensorMap* tm, int x, int y, uint32_t bar, uint16_t mask) {
  asm volatile("cp.async.bulk.tensor.2d.shared::cluster.global.mbarrier::complete_tx::bytes.multicast::cluster [%0],[%1,{%3,%4}],[%2],%5;"
               ::"r"(dst), "l"(tm), "r"(bar), "r"(x), "r"(y), "h"(mask) : "memory");
}
DEVI void bulk_load(uint32_t dst, const void* src, uint32_t bytes, uint32_t bar) {
  asm volatile("cp.async.bulk.shared::cluster.global.mbarrier::complete_tx::bytes [%0],[%1],%2,[%3];"
               ::"r"(dst), "l"(src), "r"(bytes), "r"(bar) : "memory");
}
DEVI void bulk_load_mc(uint32_t dst, const void* src, uint32_t bytes, uint32_t bar, uint16_t mask) {
  asm volatile("cp.async.bulk.shared::cluster.global.mbarrier::complete_tx::bytes.multicast::cluster [%0],[%1],%2,[%3],%4;"
               ::"r"(dst), "l"(src), "r"(bytes), "r"(bar), "h"(mask) : "memory");
}
DEVI void bulk_s2s(uint32_t dst, uint32_t src, uint32_t bytes, uint32_t bar) {
  asm volatile("cp.async.bulk.shared::cluster.shared::cta.mbarrier::complete_tx::bytes [%0],[%1],%2,[%3];"
               ::"r"(dst), "r"(src), "r"(bytes), "r"(bar) : "memory");
}
DEVI void bulk_store(void* dst, uint32_t src, uint32_t bytes) {
  asm volatile("cp.async.bulk.global.shared::cta.bulk_group [%0],[%1],%2;" ::"l"(dst), "r"(src), "r"(bytes) : "memory");
}
DEVI void bulk_commit() { asm volatile("cp.async.bulk.commit_group;" ::: "memory"); }
DEVI void bulk_wait0() { asm volatile("cp.async.bulk.wait_group 0;" ::: "memory"); }
template <int N> DEVI void bulk_wait() { asm volatile("cp.async.bulk.wait_group %0;" ::"n"(N) : "memory"); }
DEVI void st_async2(uint32_t dst, float a, float b, uint32_t bar) {
  asm volatile("st.async.weak.shared::cluster.mbarrier::complete_tx::bytes.v2.f32 [%0],{%1,%2},[%3];"
               ::"r"(dst), "f"(a), "f"(b), "r"(bar) : "memory");
}
DEVI void st_async4(uint32_t dst, uint32_t a, uint32_t b, uint32_t c, uint32_t d, uint32_t bar) {
  asm volatile("st.async.weak.shared::cluster.mbarrier::complete_tx::bytes.v4.b32 [%0],{%1,%2,%3,%4},[%5];"
               ::"r"(dst), "r"(a), "r"(b), "r"(c), "r"(d), "r"(bar) : "memory");
}
DEVI void wg_fence() { asm volatile("wgmma.fence.sync.aligned;" ::: "memory"); }
DEVI void wg_commit() { asm volatile("wgmma.commit_group.sync.aligned;" ::: "memory"); }
template <int N> DEVI void wg_wait() { asm volatile("wgmma.wait_group.sync.aligned %0;" ::"n"(N) : "memory"); }
DEVI uint64_t desc64(uint32_t lo, uint32_t hi) {
  uint64_t d;
  asm("mov.b64 %0,{%1,%2};" : "=l"(d) : "r"(lo), "r"(hi));
  return d;
}
DEVI uint32_t pin(uint32_t v) { asm volatile("" : "+r"(v)); return v; }
DEVI bool elect() {
  uint32_t p;
  asm volatile("{.reg .pred p; elect.sync _|p,0xffffffff; selp.u32 %0,1,0,p;}" : "=r"(p));
  return p;
}
DEVI int uni(int v) { return __shfl_sync(~0u, v, 0); }
DEVI void mma16816(float* c, uint32_t a0, uint32_t a1, uint32_t a2, uint32_t a3, uint32_t b0, uint32_t b1) {
  asm volatile("mma.sync.aligned.m16n8k16.row.col.f32.bf16.bf16.f32 {%0,%1,%2,%3},{%4,%5,%6,%7},{%8,%9},{%0,%1,%2,%3};"
               : "+f"(c[0]), "+f"(c[1]), "+f"(c[2]), "+f"(c[3]) : "r"(a0), "r"(a1), "r"(a2), "r"(a3), "r"(b0), "r"(b1));
}
DEVI void mma16816_z(float* c, uint32_t a0, uint32_t a1, uint32_t a2, uint32_t a3, uint32_t b0, uint32_t b1) {
  asm volatile("mma.sync.aligned.m16n8k16.row.col.f32.bf16.bf16.f32 {%0,%1,%2,%3},{%4,%5,%6,%7},{%8,%9},{%10,%10,%10,%10};"
               : "=f"(c[0]), "=f"(c[1]), "=f"(c[2]), "=f"(c[3]) : "r"(a0), "r"(a1), "r"(a2), "r"(a3), "r"(b0), "r"(b1), "f"(0.f));
}
DEVI uint32_t pack2(float lo, float hi) {
  uint32_t r;
  asm("cvt.rn.bf16x2.f32 %0,%1,%2;" : "=r"(r) : "f"(hi), "f"(lo));
  return r;
}
DEVI float bflo(uint32_t v) { return __uint_as_float(v << 16); }
DEVI float bfhi(uint32_t v) { return __uint_as_float(v & 0xffff0000u); }
DEVI void ldsm4(uint32_t* r, uint32_t a) {
  asm volatile("ldmatrix.sync.aligned.m8n8.x4.shared.b16 {%0,%1,%2,%3},[%4];" : "=r"(r[0]), "=r"(r[1]), "=r"(r[2]), "=r"(r[3]) : "r"(a) : "memory");
}
DEVI void ldsm4t(uint32_t* r, uint32_t a) {
  asm volatile("ldmatrix.sync.aligned.m8n8.x4.trans.shared.b16 {%0,%1,%2,%3},[%4];" : "=r"(r[0]), "=r"(r[1]), "=r"(r[2]), "=r"(r[3]) : "r"(a) : "memory");
}
DEVI void ldsm2t(uint32_t* r, uint32_t a) {
  asm volatile("ldmatrix.sync.aligned.m8n8.x2.trans.shared.b16 {%0,%1},[%2];" : "=r"(r[0]), "=r"(r[1]) : "r"(a) : "memory");
}
DEVI void stsm4t(uint32_t a, uint32_t r0, uint32_t r1, uint32_t r2, uint32_t r3) {
  asm volatile("stmatrix.sync.aligned.m8n8.x4.trans.shared.b16 [%0],{%1,%2,%3,%4};" ::"r"(a), "r"(r0), "r"(r1), "r"(r2), "r"(r3) : "memory");
}
DEVI void stsm4(uint32_t a, uint32_t r0, uint32_t r1, uint32_t r2, uint32_t r3) {
  asm volatile("stmatrix.sync.aligned.m8n8.x4.shared.b16 [%0],{%1,%2,%3,%4};" ::"r"(a), "r"(r0), "r"(r1), "r"(r2), "r"(r3) : "memory");
}
DEVI void stsm2t(uint32_t a, uint32_t r0, uint32_t r1) {
  asm volatile("stmatrix.sync.aligned.m8n8.x2.trans.shared.b16 [%0],{%1,%2};" ::"r"(a), "r"(r0), "r"(r1) : "memory");
}
DEVI uint32_t lds32(uint32_t a) { uint32_t v; asm volatile("ld.shared.u32 %0,[%1];" : "=r"(v) : "r"(a) : "memory"); return v; }
DEVI float2 lds64f(uint32_t a) { float2 v; asm volatile("ld.shared.v2.f32 {%0,%1},[%2];" : "=f"(v.x), "=f"(v.y) : "r"(a) : "memory"); return v; }
DEVI uint4 lds128(uint32_t a) {
  uint4 v;
  asm volatile("ld.shared.v4.u32 {%0,%1,%2,%3},[%4];" : "=r"(v.x), "=r"(v.y), "=r"(v.z), "=r"(v.w) : "r"(a) : "memory");
  return v;
}
DEVI void sts16(uint32_t a, uint32_t v) { asm volatile("st.shared.u16 [%0],%1;" ::"r"(a), "h"((uint16_t)v) : "memory"); }
DEVI void sts32(uint32_t a, uint32_t v) { asm volatile("st.shared.u32 [%0],%1;" ::"r"(a), "r"(v) : "memory"); }
DEVI void sts64f(uint32_t a, float x, float y) { asm volatile("st.shared.v2.f32 [%0],{%1,%2};" ::"r"(a), "f"(x), "f"(y) : "memory"); }
DEVI void sts128(uint32_t a, uint32_t x, uint32_t y, uint32_t z, uint32_t w) {
  asm volatile("st.shared.v4.u32 [%0],{%1,%2,%3,%4};" ::"r"(a), "r"(x), "r"(y), "r"(z), "r"(w) : "memory");
}
DEVI uint32_t hfma2(uint32_t a, uint32_t b, uint32_t c) { uint32_t d; asm("fma.rn.bf16x2 %0,%1,%2,%3;" : "=r"(d) : "r"(a), "r"(b), "r"(c)); return d; }
DEVI uint32_t hmul2(uint32_t a, uint32_t b) { uint32_t d; asm("mul.rn.bf16x2 %0,%1,%2;" : "=r"(d) : "r"(a), "r"(b)); return d; }
DEVI float ex2(float x) { float y; asm("ex2.approx.ftz.f32 %0,%1;" : "=f"(y) : "f"(x)); return y; }
DEVI float rcp(float x) { float y; asm("rcp.approx.ftz.f32 %0,%1;" : "=f"(y) : "f"(x)); return y; }

__device__ __forceinline__ void conv_mma(float* d, uint32_t da, uint32_t db) {
  asm volatile(
   "{.reg .pred p0,p1; .reg .b64 a,b; .reg .b32 x,y,ha,hb;\n"
   "setp.ne.b32 p0,0,0; setp.eq.b32 p1,0,0; mov.b32 ha,35; mov.b32 hb,8;\n"
   "wgmma.fence.sync.aligned;\n"
   "add.u32 x,%64,0; add.u32 y,%65,0; mov.b64 a,{x,ha}; mov.b64 b,{y,hb};\n"
   "wgmma.mma_async.sync.aligned.m64n128k16.f32.bf16.bf16 {%0,%1,%2,%3,%4,%5,%6,%7,%8,%9,%10,%11,%12,%13,%14,%15,%16,%17,%18,%19,%20,%21,%22,%23,%24,%25,%26,%27,%28,%29,%30,%31,%32,%33,%34,%35,%36,%37,%38,%39,%40,%41,%42,%43,%44,%45,%46,%47,%48,%49,%50,%51,%52,%53,%54,%55,%56,%57,%58,%59,%60,%61,%62,%63},a,b,p0,1,1,0,0;\n"
   "add.u32 x,%64,2; add.u32 y,%65,290; mov.b64 a,{x,ha}; mov.b64 b,{y,hb};\n"
   "wgmma.mma_async.sync.aligned.m64n128k16.f32.bf16.bf16 {%0,%1,%2,%3,%4,%5,%6,%7,%8,%9,%10,%11,%12,%13,%14,%15,%16,%17,%18,%19,%20,%21,%22,%23,%24,%25,%26,%27,%28,%29,%30,%31,%32,%33,%34,%35,%36,%37,%38,%39,%40,%41,%42,%43,%44,%45,%46,%47,%48,%49,%50,%51,%52,%53,%54,%55,%56,%57,%58,%59,%60,%61,%62,%63},a,b,p1,1,1,0,0;\n"
   "add.u32 x,%64,8; add.u32 y,%65,4; mov.b64 a,{x,ha}; mov.b64 b,{y,hb};\n"
   "wgmma.mma_async.sync.aligned.m64n128k16.f32.bf16.bf16 {%0,%1,%2,%3,%4,%5,%6,%7,%8,%9,%10,%11,%12,%13,%14,%15,%16,%17,%18,%19,%20,%21,%22,%23,%24,%25,%26,%27,%28,%29,%30,%31,%32,%33,%34,%35,%36,%37,%38,%39,%40,%41,%42,%43,%44,%45,%46,%47,%48,%49,%50,%51,%52,%53,%54,%55,%56,%57,%58,%59,%60,%61,%62,%63},a,b,p1,1,1,0,0;\n"
   "add.u32 x,%64,10; add.u32 y,%65,294; mov.b64 a,{x,ha}; mov.b64 b,{y,hb};\n"
   "wgmma.mma_async.sync.aligned.m64n128k16.f32.bf16.bf16 {%0,%1,%2,%3,%4,%5,%6,%7,%8,%9,%10,%11,%12,%13,%14,%15,%16,%17,%18,%19,%20,%21,%22,%23,%24,%25,%26,%27,%28,%29,%30,%31,%32,%33,%34,%35,%36,%37,%38,%39,%40,%41,%42,%43,%44,%45,%46,%47,%48,%49,%50,%51,%52,%53,%54,%55,%56,%57,%58,%59,%60,%61,%62,%63},a,b,p1,1,1,0,0;\n"
   "add.u32 x,%64,16; add.u32 y,%65,8; mov.b64 a,{x,ha}; mov.b64 b,{y,hb};\n"
   "wgmma.mma_async.sync.aligned.m64n128k16.f32.bf16.bf16 {%0,%1,%2,%3,%4,%5,%6,%7,%8,%9,%10,%11,%12,%13,%14,%15,%16,%17,%18,%19,%20,%21,%22,%23,%24,%25,%26,%27,%28,%29,%30,%31,%32,%33,%34,%35,%36,%37,%38,%39,%40,%41,%42,%43,%44,%45,%46,%47,%48,%49,%50,%51,%52,%53,%54,%55,%56,%57,%58,%59,%60,%61,%62,%63},a,b,p1,1,1,0,0;\n"
   "add.u32 x,%64,18; add.u32 y,%65,298; mov.b64 a,{x,ha}; mov.b64 b,{y,hb};\n"
   "wgmma.mma_async.sync.aligned.m64n128k16.f32.bf16.bf16 {%0,%1,%2,%3,%4,%5,%6,%7,%8,%9,%10,%11,%12,%13,%14,%15,%16,%17,%18,%19,%20,%21,%22,%23,%24,%25,%26,%27,%28,%29,%30,%31,%32,%33,%34,%35,%36,%37,%38,%39,%40,%41,%42,%43,%44,%45,%46,%47,%48,%49,%50,%51,%52,%53,%54,%55,%56,%57,%58,%59,%60,%61,%62,%63},a,b,p1,1,1,0,0;\n"
   "add.u32 x,%64,24; add.u32 y,%65,12; mov.b64 a,{x,ha}; mov.b64 b,{y,hb};\n"
   "wgmma.mma_async.sync.aligned.m64n128k16.f32.bf16.bf16 {%0,%1,%2,%3,%4,%5,%6,%7,%8,%9,%10,%11,%12,%13,%14,%15,%16,%17,%18,%19,%20,%21,%22,%23,%24,%25,%26,%27,%28,%29,%30,%31,%32,%33,%34,%35,%36,%37,%38,%39,%40,%41,%42,%43,%44,%45,%46,%47,%48,%49,%50,%51,%52,%53,%54,%55,%56,%57,%58,%59,%60,%61,%62,%63},a,b,p1,1,1,0,0;\n"
   "add.u32 x,%64,26; add.u32 y,%65,302; mov.b64 a,{x,ha}; mov.b64 b,{y,hb};\n"
   "wgmma.mma_async.sync.aligned.m64n128k16.f32.bf16.bf16 {%0,%1,%2,%3,%4,%5,%6,%7,%8,%9,%10,%11,%12,%13,%14,%15,%16,%17,%18,%19,%20,%21,%22,%23,%24,%25,%26,%27,%28,%29,%30,%31,%32,%33,%34,%35,%36,%37,%38,%39,%40,%41,%42,%43,%44,%45,%46,%47,%48,%49,%50,%51,%52,%53,%54,%55,%56,%57,%58,%59,%60,%61,%62,%63},a,b,p1,1,1,0,0;\n"
   "wgmma.commit_group.sync.aligned;\n"
   "wgmma.wait_group.sync.aligned 0;\n"
   "add.u32 x,%64,280; add.u32 y,%65,32; mov.b64 a,{x,ha}; mov.b64 b,{y,hb};\n"
   "wgmma.mma_async.sync.aligned.m64n96k16.f32.bf16.bf16 {%0,%1,%2,%3,%4,%5,%6,%7,%8,%9,%10,%11,%12,%13,%14,%15,%16,%17,%18,%19,%20,%21,%22,%23,%24,%25,%26,%27,%28,%29,%30,%31,%32,%33,%34,%35,%36,%37,%38,%39,%40,%41,%42,%43,%44,%45,%46,%47},a,b,p1,1,1,0,0;\n"
   "add.u32 x,%64,282; add.u32 y,%65,322; mov.b64 a,{x,ha}; mov.b64 b,{y,hb};\n"
   "wgmma.mma_async.sync.aligned.m64n96k16.f32.bf16.bf16 {%0,%1,%2,%3,%4,%5,%6,%7,%8,%9,%10,%11,%12,%13,%14,%15,%16,%17,%18,%19,%20,%21,%22,%23,%24,%25,%26,%27,%28,%29,%30,%31,%32,%33,%34,%35,%36,%37,%38,%39,%40,%41,%42,%43,%44,%45,%46,%47},a,b,p1,1,1,0,0;\n"
   "add.u32 x,%64,288; add.u32 y,%65,36; mov.b64 a,{x,ha}; mov.b64 b,{y,hb};\n"
   "wgmma.mma_async.sync.aligned.m64n96k16.f32.bf16.bf16 {%0,%1,%2,%3,%4,%5,%6,%7,%8,%9,%10,%11,%12,%13,%14,%15,%16,%17,%18,%19,%20,%21,%22,%23,%24,%25,%26,%27,%28,%29,%30,%31,%32,%33,%34,%35,%36,%37,%38,%39,%40,%41,%42,%43,%44,%45,%46,%47},a,b,p1,1,1,0,0;\n"
   "add.u32 x,%64,290; add.u32 y,%65,326; mov.b64 a,{x,ha}; mov.b64 b,{y,hb};\n"
   "wgmma.mma_async.sync.aligned.m64n96k16.f32.bf16.bf16 {%0,%1,%2,%3,%4,%5,%6,%7,%8,%9,%10,%11,%12,%13,%14,%15,%16,%17,%18,%19,%20,%21,%22,%23,%24,%25,%26,%27,%28,%29,%30,%31,%32,%33,%34,%35,%36,%37,%38,%39,%40,%41,%42,%43,%44,%45,%46,%47},a,b,p1,1,1,0,0;\n"
   "add.u32 x,%64,296; add.u32 y,%65,40; mov.b64 a,{x,ha}; mov.b64 b,{y,hb};\n"
   "wgmma.mma_async.sync.aligned.m64n96k16.f32.bf16.bf16 {%0,%1,%2,%3,%4,%5,%6,%7,%8,%9,%10,%11,%12,%13,%14,%15,%16,%17,%18,%19,%20,%21,%22,%23,%24,%25,%26,%27,%28,%29,%30,%31,%32,%33,%34,%35,%36,%37,%38,%39,%40,%41,%42,%43,%44,%45,%46,%47},a,b,p1,1,1,0,0;\n"
   "add.u32 x,%64,298; add.u32 y,%65,330; mov.b64 a,{x,ha}; mov.b64 b,{y,hb};\n"
   "wgmma.mma_async.sync.aligned.m64n96k16.f32.bf16.bf16 {%0,%1,%2,%3,%4,%5,%6,%7,%8,%9,%10,%11,%12,%13,%14,%15,%16,%17,%18,%19,%20,%21,%22,%23,%24,%25,%26,%27,%28,%29,%30,%31,%32,%33,%34,%35,%36,%37,%38,%39,%40,%41,%42,%43,%44,%45,%46,%47},a,b,p1,1,1,0,0;\n"
   "add.u32 x,%64,304; add.u32 y,%65,44; mov.b64 a,{x,ha}; mov.b64 b,{y,hb};\n"
   "wgmma.mma_async.sync.aligned.m64n96k16.f32.bf16.bf16 {%0,%1,%2,%3,%4,%5,%6,%7,%8,%9,%10,%11,%12,%13,%14,%15,%16,%17,%18,%19,%20,%21,%22,%23,%24,%25,%26,%27,%28,%29,%30,%31,%32,%33,%34,%35,%36,%37,%38,%39,%40,%41,%42,%43,%44,%45,%46,%47},a,b,p1,1,1,0,0;\n"
   "add.u32 x,%64,306; add.u32 y,%65,334; mov.b64 a,{x,ha}; mov.b64 b,{y,hb};\n"
   "wgmma.mma_async.sync.aligned.m64n96k16.f32.bf16.bf16 {%0,%1,%2,%3,%4,%5,%6,%7,%8,%9,%10,%11,%12,%13,%14,%15,%16,%17,%18,%19,%20,%21,%22,%23,%24,%25,%26,%27,%28,%29,%30,%31,%32,%33,%34,%35,%36,%37,%38,%39,%40,%41,%42,%43,%44,%45,%46,%47},a,b,p1,1,1,0,0;\n"
   "wgmma.commit_group.sync.aligned;\n"
   "wgmma.wait_group.sync.aligned 0;\n"
   "add.u32 x,%64,560; add.u32 y,%65,64; mov.b64 a,{x,ha}; mov.b64 b,{y,hb};\n"
   "wgmma.mma_async.sync.aligned.m64n64k16.f32.bf16.bf16 {%0,%1,%2,%3,%4,%5,%6,%7,%8,%9,%10,%11,%12,%13,%14,%15,%16,%17,%18,%19,%20,%21,%22,%23,%24,%25,%26,%27,%28,%29,%30,%31},a,b,p1,1,1,0,0;\n"
   "add.u32 x,%64,562; add.u32 y,%65,354; mov.b64 a,{x,ha}; mov.b64 b,{y,hb};\n"
   "wgmma.mma_async.sync.aligned.m64n64k16.f32.bf16.bf16 {%0,%1,%2,%3,%4,%5,%6,%7,%8,%9,%10,%11,%12,%13,%14,%15,%16,%17,%18,%19,%20,%21,%22,%23,%24,%25,%26,%27,%28,%29,%30,%31},a,b,p1,1,1,0,0;\n"
   "add.u32 x,%64,568; add.u32 y,%65,68; mov.b64 a,{x,ha}; mov.b64 b,{y,hb};\n"
   "wgmma.mma_async.sync.aligned.m64n64k16.f32.bf16.bf16 {%0,%1,%2,%3,%4,%5,%6,%7,%8,%9,%10,%11,%12,%13,%14,%15,%16,%17,%18,%19,%20,%21,%22,%23,%24,%25,%26,%27,%28,%29,%30,%31},a,b,p1,1,1,0,0;\n"
   "add.u32 x,%64,570; add.u32 y,%65,358; mov.b64 a,{x,ha}; mov.b64 b,{y,hb};\n"
   "wgmma.mma_async.sync.aligned.m64n64k16.f32.bf16.bf16 {%0,%1,%2,%3,%4,%5,%6,%7,%8,%9,%10,%11,%12,%13,%14,%15,%16,%17,%18,%19,%20,%21,%22,%23,%24,%25,%26,%27,%28,%29,%30,%31},a,b,p1,1,1,0,0;\n"
   "add.u32 x,%64,576; add.u32 y,%65,72; mov.b64 a,{x,ha}; mov.b64 b,{y,hb};\n"
   "wgmma.mma_async.sync.aligned.m64n64k16.f32.bf16.bf16 {%0,%1,%2,%3,%4,%5,%6,%7,%8,%9,%10,%11,%12,%13,%14,%15,%16,%17,%18,%19,%20,%21,%22,%23,%24,%25,%26,%27,%28,%29,%30,%31},a,b,p1,1,1,0,0;\n"
   "add.u32 x,%64,578; add.u32 y,%65,362; mov.b64 a,{x,ha}; mov.b64 b,{y,hb};\n"
   "wgmma.mma_async.sync.aligned.m64n64k16.f32.bf16.bf16 {%0,%1,%2,%3,%4,%5,%6,%7,%8,%9,%10,%11,%12,%13,%14,%15,%16,%17,%18,%19,%20,%21,%22,%23,%24,%25,%26,%27,%28,%29,%30,%31},a,b,p1,1,1,0,0;\n"
   "add.u32 x,%64,584; add.u32 y,%65,76; mov.b64 a,{x,ha}; mov.b64 b,{y,hb};\n"
   "wgmma.mma_async.sync.aligned.m64n64k16.f32.bf16.bf16 {%0,%1,%2,%3,%4,%5,%6,%7,%8,%9,%10,%11,%12,%13,%14,%15,%16,%17,%18,%19,%20,%21,%22,%23,%24,%25,%26,%27,%28,%29,%30,%31},a,b,p1,1,1,0,0;\n"
   "add.u32 x,%64,586; add.u32 y,%65,366; mov.b64 a,{x,ha}; mov.b64 b,{y,hb};\n"
   "wgmma.mma_async.sync.aligned.m64n64k16.f32.bf16.bf16 {%0,%1,%2,%3,%4,%5,%6,%7,%8,%9,%10,%11,%12,%13,%14,%15,%16,%17,%18,%19,%20,%21,%22,%23,%24,%25,%26,%27,%28,%29,%30,%31},a,b,p1,1,1,0,0;\n"
   "wgmma.commit_group.sync.aligned;\n"
   "wgmma.wait_group.sync.aligned 0;\n"
   "add.u32 x,%64,840; add.u32 y,%65,96; mov.b64 a,{x,ha}; mov.b64 b,{y,hb};\n"
   "wgmma.mma_async.sync.aligned.m64n32k16.f32.bf16.bf16 {%0,%1,%2,%3,%4,%5,%6,%7,%8,%9,%10,%11,%12,%13,%14,%15},a,b,p1,1,1,0,0;\n"
   "add.u32 x,%64,842; add.u32 y,%65,386; mov.b64 a,{x,ha}; mov.b64 b,{y,hb};\n"
   "wgmma.mma_async.sync.aligned.m64n32k16.f32.bf16.bf16 {%0,%1,%2,%3,%4,%5,%6,%7,%8,%9,%10,%11,%12,%13,%14,%15},a,b,p1,1,1,0,0;\n"
   "add.u32 x,%64,848; add.u32 y,%65,100; mov.b64 a,{x,ha}; mov.b64 b,{y,hb};\n"
   "wgmma.mma_async.sync.aligned.m64n32k16.f32.bf16.bf16 {%0,%1,%2,%3,%4,%5,%6,%7,%8,%9,%10,%11,%12,%13,%14,%15},a,b,p1,1,1,0,0;\n"
   "add.u32 x,%64,850; add.u32 y,%65,390; mov.b64 a,{x,ha}; mov.b64 b,{y,hb};\n"
   "wgmma.mma_async.sync.aligned.m64n32k16.f32.bf16.bf16 {%0,%1,%2,%3,%4,%5,%6,%7,%8,%9,%10,%11,%12,%13,%14,%15},a,b,p1,1,1,0,0;\n"
   "add.u32 x,%64,856; add.u32 y,%65,104; mov.b64 a,{x,ha}; mov.b64 b,{y,hb};\n"
   "wgmma.mma_async.sync.aligned.m64n32k16.f32.bf16.bf16 {%0,%1,%2,%3,%4,%5,%6,%7,%8,%9,%10,%11,%12,%13,%14,%15},a,b,p1,1,1,0,0;\n"
   "add.u32 x,%64,858; add.u32 y,%65,394; mov.b64 a,{x,ha}; mov.b64 b,{y,hb};\n"
   "wgmma.mma_async.sync.aligned.m64n32k16.f32.bf16.bf16 {%0,%1,%2,%3,%4,%5,%6,%7,%8,%9,%10,%11,%12,%13,%14,%15},a,b,p1,1,1,0,0;\n"
   "add.u32 x,%64,864; add.u32 y,%65,108; mov.b64 a,{x,ha}; mov.b64 b,{y,hb};\n"
   "wgmma.mma_async.sync.aligned.m64n32k16.f32.bf16.bf16 {%0,%1,%2,%3,%4,%5,%6,%7,%8,%9,%10,%11,%12,%13,%14,%15},a,b,p1,1,1,0,0;\n"
   "add.u32 x,%64,866; add.u32 y,%65,398; mov.b64 a,{x,ha}; mov.b64 b,{y,hb};\n"
   "wgmma.mma_async.sync.aligned.m64n32k16.f32.bf16.bf16 {%0,%1,%2,%3,%4,%5,%6,%7,%8,%9,%10,%11,%12,%13,%14,%15},a,b,p1,1,1,0,0;\n"
   "wgmma.commit_group.sync.aligned;\n"
   "wgmma.wait_group.sync.aligned 0;\n"
   "}\n"
   :"=f"(d[0]),"=f"(d[1]),"=f"(d[2]),"=f"(d[3]),"=f"(d[4]),"=f"(d[5]),"=f"(d[6]),"=f"(d[7]),"=f"(d[8]),"=f"(d[9]),"=f"(d[10]),"=f"(d[11]),"=f"(d[12]),"=f"(d[13]),"=f"(d[14]),"=f"(d[15]),"=f"(d[16]),"=f"(d[17]),"=f"(d[18]),"=f"(d[19]),"=f"(d[20]),"=f"(d[21]),"=f"(d[22]),"=f"(d[23]),"=f"(d[24]),"=f"(d[25]),"=f"(d[26]),"=f"(d[27]),"=f"(d[28]),"=f"(d[29]),"=f"(d[30]),"=f"(d[31]),"=f"(d[32]),"=f"(d[33]),"=f"(d[34]),"=f"(d[35]),"=f"(d[36]),"=f"(d[37]),"=f"(d[38]),"=f"(d[39]),"=f"(d[40]),"=f"(d[41]),"=f"(d[42]),"=f"(d[43]),"=f"(d[44]),"=f"(d[45]),"=f"(d[46]),"=f"(d[47]),"=f"(d[48]),"=f"(d[49]),"=f"(d[50]),"=f"(d[51]),"=f"(d[52]),"=f"(d[53]),"=f"(d[54]),"=f"(d[55]),"=f"(d[56]),"=f"(d[57]),"=f"(d[58]),"=f"(d[59]),"=f"(d[60]),"=f"(d[61]),"=f"(d[62]),"=f"(d[63])
   :"r"(da),"r"(db):"memory");
}

__device__ __forceinline__ void wr_n152(float* d, uint32_t a0, uint32_t a1, uint32_t a2, uint64_t db) {
  asm volatile("{.reg .pred p; setp.eq.b32 p,0,0;\n"
   "wgmma.mma_async.sync.aligned.m64n152k16.f32.bf16.bf16 {%0,%1,%2,%3,%4,%5,%6,%7,%8,%9,%10,%11,%12,%13,%14,%15,%16,%17,%18,%19,%20,%21,%22,%23,%24,%25,%26,%27,%28,%29,%30,%31,%32,%33,%34,%35,%36,%37,%38,%39,%40,%41,%42,%43,%44,%45,%46,%47,%48,%49,%50,%51,%52,%53,%54,%55,%56,%57,%58,%59,%60,%61,%62,%63,%64,%65,%66,%67,%68,%69,%70,%71,%72,%73,%74,%75},{%76,%77,%78,%78},%79,p,1,1,0;}"
   :"+f"(d[0]),"+f"(d[1]),"+f"(d[2]),"+f"(d[3]),"+f"(d[4]),"+f"(d[5]),"+f"(d[6]),"+f"(d[7]),"+f"(d[8]),"+f"(d[9]),"+f"(d[10]),"+f"(d[11]),"+f"(d[12]),"+f"(d[13]),"+f"(d[14]),"+f"(d[15]),"+f"(d[16]),"+f"(d[17]),"+f"(d[18]),"+f"(d[19]),"+f"(d[20]),"+f"(d[21]),"+f"(d[22]),"+f"(d[23]),"+f"(d[24]),"+f"(d[25]),"+f"(d[26]),"+f"(d[27]),"+f"(d[28]),"+f"(d[29]),"+f"(d[30]),"+f"(d[31]),"+f"(d[32]),"+f"(d[33]),"+f"(d[34]),"+f"(d[35]),"+f"(d[36]),"+f"(d[37]),"+f"(d[38]),"+f"(d[39]),"+f"(d[40]),"+f"(d[41]),"+f"(d[42]),"+f"(d[43]),"+f"(d[44]),"+f"(d[45]),"+f"(d[46]),"+f"(d[47]),"+f"(d[48]),"+f"(d[49]),"+f"(d[50]),"+f"(d[51]),"+f"(d[52]),"+f"(d[53]),"+f"(d[54]),"+f"(d[55]),"+f"(d[56]),"+f"(d[57]),"+f"(d[58]),"+f"(d[59]),"+f"(d[60]),"+f"(d[61]),"+f"(d[62]),"+f"(d[63]),"+f"(d[64]),"+f"(d[65]),"+f"(d[66]),"+f"(d[67]),"+f"(d[68]),"+f"(d[69]),"+f"(d[70]),"+f"(d[71]),"+f"(d[72]),"+f"(d[73]),"+f"(d[74]),"+f"(d[75])
   :"r"(a0),"r"(a1),"r"(a2),"l"(db));
}
__device__ __forceinline__ void wr_n144(float* d, uint32_t a0, uint32_t a1, uint32_t a2, uint64_t db) {
  asm volatile("{.reg .pred p; setp.eq.b32 p,0,0;\n"
   "wgmma.mma_async.sync.aligned.m64n144k16.f32.bf16.bf16 {%0,%1,%2,%3,%4,%5,%6,%7,%8,%9,%10,%11,%12,%13,%14,%15,%16,%17,%18,%19,%20,%21,%22,%23,%24,%25,%26,%27,%28,%29,%30,%31,%32,%33,%34,%35,%36,%37,%38,%39,%40,%41,%42,%43,%44,%45,%46,%47,%48,%49,%50,%51,%52,%53,%54,%55,%56,%57,%58,%59,%60,%61,%62,%63,%64,%65,%66,%67,%68,%69,%70,%71},{%72,%73,%74,%74},%75,p,1,1,0;}"
   :"+f"(d[0]),"+f"(d[1]),"+f"(d[2]),"+f"(d[3]),"+f"(d[4]),"+f"(d[5]),"+f"(d[6]),"+f"(d[7]),"+f"(d[8]),"+f"(d[9]),"+f"(d[10]),"+f"(d[11]),"+f"(d[12]),"+f"(d[13]),"+f"(d[14]),"+f"(d[15]),"+f"(d[16]),"+f"(d[17]),"+f"(d[18]),"+f"(d[19]),"+f"(d[20]),"+f"(d[21]),"+f"(d[22]),"+f"(d[23]),"+f"(d[24]),"+f"(d[25]),"+f"(d[26]),"+f"(d[27]),"+f"(d[28]),"+f"(d[29]),"+f"(d[30]),"+f"(d[31]),"+f"(d[32]),"+f"(d[33]),"+f"(d[34]),"+f"(d[35]),"+f"(d[36]),"+f"(d[37]),"+f"(d[38]),"+f"(d[39]),"+f"(d[40]),"+f"(d[41]),"+f"(d[42]),"+f"(d[43]),"+f"(d[44]),"+f"(d[45]),"+f"(d[46]),"+f"(d[47]),"+f"(d[48]),"+f"(d[49]),"+f"(d[50]),"+f"(d[51]),"+f"(d[52]),"+f"(d[53]),"+f"(d[54]),"+f"(d[55]),"+f"(d[56]),"+f"(d[57]),"+f"(d[58]),"+f"(d[59]),"+f"(d[60]),"+f"(d[61]),"+f"(d[62]),"+f"(d[63]),"+f"(d[64]),"+f"(d[65]),"+f"(d[66]),"+f"(d[67]),"+f"(d[68]),"+f"(d[69]),"+f"(d[70]),"+f"(d[71])
   :"r"(a0),"r"(a1),"r"(a2),"l"(db));
}

__device__ __forceinline__ void wg_n72(float* d, uint64_t da, uint64_t db, int sd) {
  asm volatile("{.reg .pred p; setp.ne.b32 p,%38,0;\n"
   "wgmma.mma_async.sync.aligned.m64n72k16.f32.bf16.bf16 {%0,%1,%2,%3,%4,%5,%6,%7,%8,%9,%10,%11,%12,%13,%14,%15,%16,%17,%18,%19,%20,%21,%22,%23,%24,%25,%26,%27,%28,%29,%30,%31,%32,%33,%34,%35},%36,%37,p,1,1,1,0;}"
   :"+f"(d[0]),"+f"(d[1]),"+f"(d[2]),"+f"(d[3]),"+f"(d[4]),"+f"(d[5]),"+f"(d[6]),"+f"(d[7]),"+f"(d[8]),"+f"(d[9]),"+f"(d[10]),"+f"(d[11]),"+f"(d[12]),"+f"(d[13]),"+f"(d[14]),"+f"(d[15]),"+f"(d[16]),"+f"(d[17]),"+f"(d[18]),"+f"(d[19]),"+f"(d[20]),"+f"(d[21]),"+f"(d[22]),"+f"(d[23]),"+f"(d[24]),"+f"(d[25]),"+f"(d[26]),"+f"(d[27]),"+f"(d[28]),"+f"(d[29]),"+f"(d[30]),"+f"(d[31]),"+f"(d[32]),"+f"(d[33]),"+f"(d[34]),"+f"(d[35])
   :"l"(da),"l"(db),"r"(sd));
}
__device__ __forceinline__ void wg_n144(float* d, uint64_t da, uint64_t db, int sd) {
  asm volatile("{.reg .pred p; setp.ne.b32 p,%74,0;\n"
   "wgmma.mma_async.sync.aligned.m64n144k16.f32.bf16.bf16 {%0,%1,%2,%3,%4,%5,%6,%7,%8,%9,%10,%11,%12,%13,%14,%15,%16,%17,%18,%19,%20,%21,%22,%23,%24,%25,%26,%27,%28,%29,%30,%31,%32,%33,%34,%35,%36,%37,%38,%39,%40,%41,%42,%43,%44,%45,%46,%47,%48,%49,%50,%51,%52,%53,%54,%55,%56,%57,%58,%59,%60,%61,%62,%63,%64,%65,%66,%67,%68,%69,%70,%71},%72,%73,p,1,1,1,0;}"
   :"+f"(d[0]),"+f"(d[1]),"+f"(d[2]),"+f"(d[3]),"+f"(d[4]),"+f"(d[5]),"+f"(d[6]),"+f"(d[7]),"+f"(d[8]),"+f"(d[9]),"+f"(d[10]),"+f"(d[11]),"+f"(d[12]),"+f"(d[13]),"+f"(d[14]),"+f"(d[15]),"+f"(d[16]),"+f"(d[17]),"+f"(d[18]),"+f"(d[19]),"+f"(d[20]),"+f"(d[21]),"+f"(d[22]),"+f"(d[23]),"+f"(d[24]),"+f"(d[25]),"+f"(d[26]),"+f"(d[27]),"+f"(d[28]),"+f"(d[29]),"+f"(d[30]),"+f"(d[31]),"+f"(d[32]),"+f"(d[33]),"+f"(d[34]),"+f"(d[35]),"+f"(d[36]),"+f"(d[37]),"+f"(d[38]),"+f"(d[39]),"+f"(d[40]),"+f"(d[41]),"+f"(d[42]),"+f"(d[43]),"+f"(d[44]),"+f"(d[45]),"+f"(d[46]),"+f"(d[47]),"+f"(d[48]),"+f"(d[49]),"+f"(d[50]),"+f"(d[51]),"+f"(d[52]),"+f"(d[53]),"+f"(d[54]),"+f"(d[55]),"+f"(d[56]),"+f"(d[57]),"+f"(d[58]),"+f"(d[59]),"+f"(d[60]),"+f"(d[61]),"+f"(d[62]),"+f"(d[63]),"+f"(d[64]),"+f"(d[65]),"+f"(d[66]),"+f"(d[67]),"+f"(d[68]),"+f"(d[69]),"+f"(d[70]),"+f"(d[71])
   :"l"(da),"l"(db),"r"(sd));
}
__device__ __forceinline__ void wg_n152(float* d, uint64_t da, uint64_t db, int sd) {
  asm volatile("{.reg .pred p; setp.ne.b32 p,%78,0;\n"
   "wgmma.mma_async.sync.aligned.m64n152k16.f32.bf16.bf16 {%0,%1,%2,%3,%4,%5,%6,%7,%8,%9,%10,%11,%12,%13,%14,%15,%16,%17,%18,%19,%20,%21,%22,%23,%24,%25,%26,%27,%28,%29,%30,%31,%32,%33,%34,%35,%36,%37,%38,%39,%40,%41,%42,%43,%44,%45,%46,%47,%48,%49,%50,%51,%52,%53,%54,%55,%56,%57,%58,%59,%60,%61,%62,%63,%64,%65,%66,%67,%68,%69,%70,%71,%72,%73,%74,%75},%76,%77,p,1,1,1,0;}"
   :"+f"(d[0]),"+f"(d[1]),"+f"(d[2]),"+f"(d[3]),"+f"(d[4]),"+f"(d[5]),"+f"(d[6]),"+f"(d[7]),"+f"(d[8]),"+f"(d[9]),"+f"(d[10]),"+f"(d[11]),"+f"(d[12]),"+f"(d[13]),"+f"(d[14]),"+f"(d[15]),"+f"(d[16]),"+f"(d[17]),"+f"(d[18]),"+f"(d[19]),"+f"(d[20]),"+f"(d[21]),"+f"(d[22]),"+f"(d[23]),"+f"(d[24]),"+f"(d[25]),"+f"(d[26]),"+f"(d[27]),"+f"(d[28]),"+f"(d[29]),"+f"(d[30]),"+f"(d[31]),"+f"(d[32]),"+f"(d[33]),"+f"(d[34]),"+f"(d[35]),"+f"(d[36]),"+f"(d[37]),"+f"(d[38]),"+f"(d[39]),"+f"(d[40]),"+f"(d[41]),"+f"(d[42]),"+f"(d[43]),"+f"(d[44]),"+f"(d[45]),"+f"(d[46]),"+f"(d[47]),"+f"(d[48]),"+f"(d[49]),"+f"(d[50]),"+f"(d[51]),"+f"(d[52]),"+f"(d[53]),"+f"(d[54]),"+f"(d[55]),"+f"(d[56]),"+f"(d[57]),"+f"(d[58]),"+f"(d[59]),"+f"(d[60]),"+f"(d[61]),"+f"(d[62]),"+f"(d[63]),"+f"(d[64]),"+f"(d[65]),"+f"(d[66]),"+f"(d[67]),"+f"(d[68]),"+f"(d[69]),"+f"(d[70]),"+f"(d[71]),"+f"(d[72]),"+f"(d[73]),"+f"(d[74]),"+f"(d[75])
   :"l"(da),"l"(db),"r"(sd));
}


template <int N> DEVI void fence_regs(float* d) {
#pragma unroll
  for (int i = 0; i < N; i++) asm volatile("" : "+f"(d[i])::"memory");
}

struct KvRegs { uint32_t u[8][2]; };
struct KvAddr { uint32_t k[11], v, t; };
DEVI void kv_addr(KvAddr& ad, int lane) {
  const int a = lane >> 1;
  const uint32_t hf = (lane & 1) * 8;
#pragma unroll
  for (int i = 0; i < 11; i++) {
    const int row = i < 3 ? (5 + i) * 17 + a : (i - 3) * 17 + a + 1;
    ad.k[i] = pin(row * 64 + (((row >> 1) & 3) << 4) + hf);
  }
  ad.v = pin(KIN + a * 64 + (((a >> 1) & 3) << 4) + hf);
  ad.t = pin(KIN + VIN + hf * 4);
}
DEVI void kv_load(uint32_t buf, const CUtensorMap* tmK, const CUtensorMap* tmV, const __nv_bfloat16* shp, int ch, int rc, uint32_t bar) {
  tma3d(buf, tmK, ch, rc * 16 - 1, 0, bar);
  tma3d(buf + KIN, tmV, ch, rc * 16, 0, bar);
  bulk_load(buf + KIN + VIN, shp + ch * 4, 256, bar);
}
DEVI void kv_compute(KvRegs& o, const KvAddr& ad, uint32_t buf, int col) {
  uint2 kr[11], vr[8];
#pragma unroll
  for (int i = 0; i < 11; i++)
    asm volatile("ld.shared.v2.u32 {%0,%1},[%2];" : "=r"(kr[i].x), "=r"(kr[i].y) : "r"(buf + (ad.k[i] ^ (col << 4))) : "memory");
  const uint4 w0 = lds128(buf + ad.t + col * 64), w1 = lds128(buf + ad.t + col * 64 + 16);
#pragma unroll
  for (int i = 0; i < 8; i++)
    asm volatile("ld.shared.v2.u32 {%0,%1},[%2];" : "=r"(vr[i].x), "=r"(vr[i].y) : "r"(buf + (ad.v ^ (col << 4)) + i * 1024) : "memory");
  const uint32_t t0 = __byte_perm(w0.x, w0.z, 0x5410), t1 = __byte_perm(w0.x, w0.z, 0x7632), t2 = __byte_perm(w0.y, w0.w, 0x5410),
                 t3 = __byte_perm(w0.y, w0.w, 0x7632), s0 = __byte_perm(w1.x, w1.z, 0x5410), s1 = __byte_perm(w1.x, w1.z, 0x7632),
                 s2 = __byte_perm(w1.y, w1.w, 0x5410), s3 = __byte_perm(w1.y, w1.w, 0x7632);
#pragma unroll
  for (int i = 0; i < 8; i++) {
    o.u[i][0] = hmul2(hfma2(kr[i + 3].x, t0, hfma2(kr[i + 2].x, t1, hfma2(kr[i + 1].x, t2, hmul2(kr[i].x, t3)))), vr[i].x);
    o.u[i][1] = hmul2(hfma2(kr[i + 3].y, s0, hfma2(kr[i + 2].y, s1, hfma2(kr[i + 1].y, s2, hmul2(kr[i].y, s3)))), vr[i].y);
  }
}
DEVI uint4 kv_pack(const KvRegs& o, int ch) {
  const uint32_t sel = (ch & 1) ? 0x7632 : 0x5410;
  const int cp = ch >> 1;
  return make_uint4(__byte_perm(o.u[7][cp], o.u[6][cp], sel), __byte_perm(o.u[5][cp], o.u[4][cp], sel),
                    __byte_perm(o.u[3][cp], o.u[2][cp], sel), __byte_perm(o.u[1][cp], o.u[0][cp], sel));
}
DEVI void kv_store(const KvRegs& o, int ch8, int rc, int lane) {
  uint4* dst = (uint4*)g_U + (size_t)(ch8 + (lane & 1) * 4) * 256 + (255 - rc * 16 - (lane >> 1));
#pragma unroll
  for (int ch = 0; ch < 4; ch++) __stcg(dst + ch * 256, kv_pack(o, ch));
}
DEVI void kv_publish(int lane) {
  asm volatile("fence.acq_rel.gpu;" ::: "memory");
  __syncwarp();
  if (lane == 0) asm volatile("red.relaxed.gpu.global.add.u32 [%0],%1;" ::"l"(&g_ucnt), "r"(1u) : "memory");
}

template <int NT_> struct HRegs { static constexpr int K = (280 + NT_ - 1) / NT_; uint4 A[K], B[K]; uint32_t d; };
template <int NT_>
DEVI void conv_load_h(HRegs<NT_>& r, const __nv_bfloat16* h, const __nv_bfloat16* dp, int tid, bool act = true) {
  r.d = 0;
  if (act) r.d = *(const unsigned short*)dp;
#pragma unroll
  for (int k = 0; k < HRegs<NT_>::K; k++) r.A[k] = r.B[k] = make_uint4(0, 0, 0, 0);
  if (act) {
#pragma unroll
    for (int k = 0; k < HRegs<NT_>::K; k++) {
      const int idx = min(tid + NT_ * k, 279), m = (idx * 1873) >> 16, z = idx - 3 * m - 4;
      const uint4* p = (const uint4*)h + z;
      if (k > 0 || z >= 0) r.A[k] = __ldg(p);
      if (k > 0 || z >= -1) r.B[k] = __ldg(p + 1);
    }
  }
}
template <int NT_>
DEVI void conv_expand_h(const HRegs<NT_>& r, uint32_t hs, int tid) {
#pragma unroll
  for (int k = 0; k < HRegs<NT_>::K; k++) {
    const int idx = tid + NT_ * k, m = (idx * 1873) >> 16;
    const uint32_t a = hs + idx * 16 + (m >> 1) * (4480 - 2 * HCP);
    const uint4 A = r.A[k];
    uint4 B = r.B[k];
    if (k == 0 && tid == 3) B.x = __byte_perm(pack2(bflo(B.x) + bflo(r.d), 0.f), B.x, 0x7610);
    if (idx < 280) {
      sts128(a, A.y, A.z, A.w, B.x);
      sts128(a + 2 * HCP, A.z, A.w, B.x, B.y);
      sts128(a + 4 * HCP, A.w, B.x, B.y, B.z);
      sts128(a + 6 * HCP, B.x, B.y, B.z, B.w);
      if (A.x == 0xffffffffu) sts32(a, A.y);
    }
  }
}
struct URegs { uint4 v[2]; uint32_t n[2]; };
DEVI int u_chunk(int tid) { return (tid & 0x70) | ((tid & 3) << 2) | ((tid >> 2) & 3); }
DEVI void conv_load_u(URegs& r, const __nv_bfloat16* u, int tid) {
  const int z = u_chunk(tid);
  r.v[0] = __ldcg((const uint4*)u + z);
  r.v[1] = __ldcg((const uint4*)u + z + 128);
  r.n[0] = __ldcg((const uint32_t*)u + 4 * z + 4);
  r.n[1] = z == 127 ? 0u : __ldcg((const uint32_t*)u + 4 * z + 516);
}
DEVI void conv_load_u_smem(URegs& r, uint32_t u, int tid) {
  const uint32_t a = u + u_chunk(tid) * 16;
  r.v[0] = lds128(a);
  r.v[1] = lds128(a + 2048);
  r.n[0] = lds32(a + 16);
  r.n[1] = u_chunk(tid) == 127 ? 0u : lds32(a + 2064);
}
DEVI void conv_build_u(const URegs& r, uint32_t us, int tid) {
  const int z = u_chunk(tid);
  const uint32_t a = us + (z & 3) * UAP + (z >> 2) * 32;
#pragma unroll
  for (int k = 0; k < 2; k++) {
    const uint4 v = r.v[k];
    sts128(a + k * 1024, __funnelshift_r(v.x, v.y, 16), __funnelshift_r(v.y, v.z, 16), __funnelshift_r(v.z, v.w, 16),
           __funnelshift_r(v.w, r.n[k], 16));
    sts128(a + k * 1024 + 16, v.x, v.y, v.z, v.w);
  }
  if (tid < 64) sts128(us + (tid >> 4) * UAP + 2048 + (tid & 15) * 16, 0, 0, 0, 0);
}
DEVI void conv_channel(uint32_t hs, uint32_t us, uint32_t ys, int barid, int w, int lane, uint32_t donebar) {
  static_assert(HCP == 560 && UAP == 2320, "conv_mma has the table pitches built in");
  float acc[64];
  conv_mma(acc, ((hs & 0x3FFFF) >> 4) | (1u << 16), ((us & 0x3FFFF) >> 4) | ((uint32_t)(UAP >> 4) << 16));
  if (donebar) {
    if (lane == 0) mbar_arrive_n(donebar, 2);
  } else {
    bar_sync(barid, 128);
  }
  const int t = lane & 3;
  const bool q = lane & 16, up = !q && t == 3, dn = q && t == 0;
  const int src = ((lane ^ 16) & 28) | ((q ? t + 3 : t + 1) & 3);
  float keep[16], recv[16];
#pragma unroll
  for (int j = 0; j < 16; j++) {
    const float e0 = j < 14 ? acc[4 * j] + acc[4 * j + 10] : acc[4 * j], e1 = j < 14 ? acc[4 * j + 1] + acc[4 * j + 11] : acc[4 * j + 1];
    keep[j] = q ? e1 : e0;
    recv[j] = __shfl_sync(~0u, q ? e0 : e1, src);
  }
  const uint32_t a = ys + (q ? 2048 + 32 : 0) + (63 - t) * 32 + ((lane >> 2) & 3) * 8 + w * 2;
#pragma unroll
  for (int j = 0; j < 16; j += 2) {
    float v0 = up ? recv[j + 1] : recv[j], v1 = up ? (j + 2 < 16 ? recv[j + 2] : 0.f) : recv[j + 1];
    v0 = dn ? recv[(j + 15) & 15] : v0;
    v1 = dn ? recv[j] : v1;
    v0 += (j == 0 && dn) ? 0.f : keep[j];
    const uint32_t p = pack2(v0, v1 + keep[j + 1]);
    sts16((j == 0 && dn) ? a - 2048 : a - j * 128, p);
    sts16(a - j * 128 - 128, p >> 16);
  }
}

constexpr int SMEM_SIDE = 4 * (18432 + 9728) + 1024;
__global__ void __launch_bounds__(512) side_kernel(const __grid_constant__ CUtensorMap tmK, const __grid_constant__ CUtensorMap tmV,
                                                   const __nv_bfloat16* __restrict__ shp, const __nv_bfloat16* __restrict__ hp,
                                                   const __nv_bfloat16* __restrict__ Dp, int mode, int unit0, int ch_base, int utarget) {
  extern __shared__ __align__(1024) uint8_t smraw[];
  const uint32_t sb = s2u(smraw);
  const uint32_t bar = sb + SMEM_SIDE - 1024;
  const int tid = threadIdx.x, lane = tid & 31, warp = uni(tid >> 5);
  const uint32_t t0 = clk32();
  if (mode & 1) {
    const int u = unit0 + blockIdx.x;
    if (tid == 0) {
      mbar_init(bar, 1);
      fence_async_smem();
      mbar_expect(bar, 2 * KVIN);
      kv_load(sb, &tmK, &tmV, shp, (u >> 3) * 32, (u & 7) * 2, bar);
      kv_load(sb + 18432, &tmK, &tmV, shp, (u >> 3) * 32, (u & 7) * 2 + 1, bar);
    }
    __syncthreads();
    if (warp < 8) {
      mbar_wait(bar, 0, t0);
      KvRegs o;
      KvAddr ad;
      kv_addr(ad, lane);
      kv_compute(o, ad, sb + (warp >> 2) * 18432, warp & 3);
      kv_store(o, (u >> 3) * 32 + (warp & 3) * 8, (u & 7) * 2 + (warp >> 2), lane);
      asm volatile("fence.acq_rel.gpu;" ::: "memory");
    }
    __syncthreads();
    if (warp == 0) kv_publish(lane);
  }
  if (!(mode & 2)) return;
  const int wg = warp >> 2, ch = ch_base + blockIdx.x * 4 + wg;
  const uint32_t hs = sb + wg * (18432 + 9728), us = hs + 18432;
  HRegs<128> hr;
  conv_load_h(hr, hp + (size_t)ch * 2048, Dp + ch, tid & 127);
  conv_expand_h(hr, hs, tid & 127);
  flag_wait(&g_ucnt, utarget, t0);
  URegs ur;
  conv_load_u(ur, g_U + (size_t)ch * 2048, tid & 127);
  conv_build_u(ur, us, tid & 127);
  fence_async_smem();
  bar_sync(1 + wg, 128);
  conv_channel(hs, us, hs, 1 + wg, warp & 3, lane, 0u);
  fence_async_smem();
  bar_sync(1 + wg, 128);
  if ((tid & 127) == 0) {
    bulk_store(g_Y + (size_t)ch * 2048, hs, 4096);
    bulk_commit();
    bulk_wait0();
    asm volatile("red.relaxed.gpu.global.add.u32 [%0],%1;" ::"l"(&g_ycnt[ch >> 6]), "r"(1u) : "memory");
  }
}

struct Ctx {
  uint32_t sb;
  uint32_t t0;
};
DEVI uint32_t barx(const Ctx& c, int i) { return c.sb + OFF_BAR + 8 * i; }
DEVI uint32_t xslot(const Ctx& c, int p) { return c.sb + OFF_X + p * XSLOT; }
DEVI void bwait(const Ctx& c, int i, uint32_t ph) { mbar_wait(barx(c, i), ph, c.t0); }
DEVI void cluster_wait() { asm volatile("barrier.cluster.wait.aligned;" ::: "memory"); }

DEVI int ord(int rank, int i) { return i == 0 ? rank : (i <= rank ? i - 1 : i); }

DEVI float2 row_stats(const uint32_t* f, int lane) {
  const uint32_t ones = 0x3f803f80u;
  float d[8];
  mma16816_z(d, f[0], ones, f[1], ones, f[0], f[1]);
  mma16816_z(d + 4, f[4], ones, f[5], ones, f[4], f[5]);
  mma16816(d, f[2], ones, f[3], ones, f[2], f[3]);
  mma16816(d + 4, f[6], ones, f[7], ones, f[6], f[7]);
  const bool odd = lane & 4;
  return make_float2(odd ? d[3] + d[7] : d[2] + d[6], odd ? d[1] + d[5] : d[0] + d[4]);
}
DEVI void stats_send(float2 v, uint32_t dst, uint32_t bar, int lane) {
  const int src = (lane & 28) | (lane >> 3);
  v.x = __shfl_sync(~0u, v.x, src);
  v.y = __shfl_sync(~0u, v.y, src);
  st_async2(mapa(dst, lane & 3), v.x, v.y, mapa(bar, lane & 3));
  st_async2(mapa(dst, (lane & 3) + 4), v.x, v.y, mapa(bar, (lane & 3) + 4));
}
DEVI float2 finish_stats(uint32_t a, int pitch) {
  float2 v[8];
#pragma unroll
  for (int p = 0; p < 8; p++) v[p] = lds64f(a + p * pitch);
  const float s = ((v[0].x + v[1].x) + (v[2].x + v[3].x)) + ((v[4].x + v[5].x) + (v[6].x + v[7].x));
  const float q = ((v[0].y + v[1].y) + (v[2].y + v[3].y)) + ((v[4].y + v[5].y) + (v[6].y + v[7].y));
  const float mean = s * (1.f / 512.f);
  const float var = fmaxf(q * (1.f / 512.f) - mean * mean, 0.f);
  float r;
  asm("rsqrt.approx.ftz.f32 %0,%1;" : "=f"(r) : "f"(var + 1e-5f));
  return make_float2(r, -mean);
}

DEVI void attention(const Ctx& c, uint32_t qa, uint32_t qh, uint32_t ka, uint32_t va, uint32_t oa, uint32_t ra, int lane, int layer,
                    bool first, bool kfree, int vbar, int cnt) {
  const int g = lane >> 2, t = lane & 3;
  uint32_t kf[10][2], vf[10][2], qf[5][4];
  const bool prev0 = 2 * t > g, prev1 = 2 * t + 1 > g;
  const uint32_t mprev = (prev0 ? 0xffffu : 0u) | (prev1 ? 0xffff0000u : 0u);
  const float sc2 = 0.25f * 1.4426950408889634f;
  float rq[9], rk[9][2];
#pragma unroll
  for (int j = 0; j < 9; j++) {
    rq[j] = __uint_as_float(lds32(ra + g * 4 + j * 32)) * sc2;
    rk[j][0] = __uint_as_float(lds32(ra + t * 8 - (prev0 ? 32 : 0) + j * 32));
    rk[j][1] = __uint_as_float(lds32(ra + t * 8 + 4 - (prev1 ? 32 : 0) + j * 32));
  }
  bwait(c, B_KQST, layer);
#pragma unroll
  for (int u = 0; u < 5; u++) { ldsm4(qf[u], (u < 4 ? qa : qh) + u * 512); ldsm4(&kf[2 * u][0], ka + u * 512); }
  bwait(c, B_VDONE, layer);
  float l[9][2], mx[9];
#pragma unroll
  for (int u = 0; u < 5; u++) {
    float s0[4], s1[4], s2[4];
    mma16816_z(s0, qf[u][0], qf[u][1], qf[u][2], qf[u][3], kf[2 * u][0], kf[2 * u][1]);
    mma16816_z(s1, qf[u][0], qf[u][1], qf[u][2], qf[u][3], kf[2 * u + 1][0], kf[2 * u + 1][1]);
    if (u == 0 && first) { s0[0] = -INFINITY; s0[1] = -INFINITY; }
    l[2 * u][0] = (prev0 ? s0[0] : s1[0]) * rk[2 * u][0];
    l[2 * u][1] = (prev1 ? s0[1] : s1[1]) * rk[2 * u][1];
    if (u < 4) {
      mma16816_z(s2, qf[u][0], qf[u][1], qf[u][2], qf[u][3], kf[2 * u + 2][0], kf[2 * u + 2][1]);
      l[2 * u + 1][0] = (prev0 ? s1[2] : s2[2]) * rk[2 * u + 1][0];
      l[2 * u + 1][1] = (prev1 ? s1[3] : s2[3]) * rk[2 * u + 1][1];
    }
  }
#pragma unroll
  for (int j = 0; j < 9; j++) mx[j] = fmaxf(l[j][0], l[j][1]);
#pragma unroll
  for (int j = 0; j < 9; j++) mx[j] = fmaxf(mx[j], __shfl_xor_sync(~0u, mx[j], 1));
#pragma unroll
  for (int j = 0; j < 9; j++) mx[j] = -rq[j] * fmaxf(mx[j], __shfl_xor_sync(~0u, mx[j], 2));
  const uint32_t ones = 0x3f803f80u;
  uint32_t pp[9];
  float rs[9][2];
#pragma unroll
  for (int j = 0; j < 9; j++) {
    const float e0 = ex2(fmaf(l[j][0], rq[j], mx[j])), e1 = ex2(fmaf(l[j][1], rq[j], mx[j]));
    float sm[4];
    asm volatile("mma.sync.aligned.m16n8k8.row.col.f32.bf16.bf16.f32 {%0,%1,%2,%3},{%4,%4},{%5},{%6,%6,%6,%6};"
                 : "=f"(sm[0]), "=f"(sm[1]), "=f"(sm[2]), "=f"(sm[3]) : "r"(ones), "r"(pack2(e0, e1)), "f"(0.f));
    pp[j] = pack2(e0 * rk[j][0], e1 * rk[j][1]);
    const float r = rcp(sm[0] * sm[1]);
    rs[j][0] = r * sm[1];
    rs[j][1] = r * sm[0];
  }
  bar_sync(vbar, 64);
#pragma unroll
  for (int u = 0; u < 5; u++) ldsm4t(&vf[2 * u][0], va + u * 512);
  if (kfree) bwait(c, B_KFREE, 0);
  if (layer) {
    reads_done();
    __syncwarp();
    if (lane == 0) mbar_arrive_n(barx(c, B_X2ST), cnt);
  }
  uint32_t o[10][2];
#pragma unroll
  for (int j = 0; j < 9; j++) {
    float d[4];
    if (j & 1) {
      asm volatile("mma.sync.aligned.m16n8k8.row.col.f32.bf16.bf16.f32 {%0,%1,%2,%3},{%4,%5},{%6},{%7,%7,%7,%7};"
                   : "=f"(d[0]), "=f"(d[1]), "=f"(d[2]), "=f"(d[3]) : "r"(vf[j][0]), "r"(vf[j][1]), "r"(pp[j] & mprev), "f"(0.f));
      asm volatile("mma.sync.aligned.m16n8k8.row.col.f32.bf16.bf16.f32 {%0,%1,%2,%3},{%4,%5},{%6},{%0,%1,%2,%3};"
                   : "+f"(d[0]), "+f"(d[1]), "+f"(d[2]), "+f"(d[3]) : "r"(vf[j + 1][0]), "r"(vf[j + 1][1]), "r"(pp[j] & ~mprev));
    } else {
      mma16816_z(d, vf[j][0], vf[j][1], vf[j + 1][0], vf[j + 1][1], pp[j] & mprev, pp[j] & ~mprev);
    }
    o[j][0] = pack2(d[0] * rs[j][0], d[1] * rs[j][1]);
    o[j][1] = pack2(d[2] * rs[j][0], d[3] * rs[j][1]);
    if (j & 1) stsm4t(oa + (j - 1) * 256, o[j - 1][0], o[j - 1][1], o[j][0], o[j][1]);
  }
  stsm2t(oa + 2048, o[8][0], o[8][1]);
  fence_async_smem();
  __syncwarp();
  if (lane == 0) mbar_arrive_n(barx(c, B_STAGED), cnt);
}


__global__ void __cluster_dims__(8, 1, 1) __launch_bounds__(512, 1)
main_kernel(const __grid_constant__ CUtensorMap tmX72, const __grid_constant__ CUtensorMap tmX7,
            const __grid_constant__ CUtensorMap tmW, const __grid_constant__ CUtensorMap tmWo,
            const __grid_constant__ CUtensorMap tmWo3,
            const __grid_constant__ CUtensorMap tmY, const __grid_constant__ CUtensorMap tmK,
            const __grid_constant__ CUtensorMap tmV, __nv_bfloat16* __restrict__ outp,
            const __nv_bfloat16* __restrict__ wqkvp, const __nv_bfloat16* __restrict__ wop,
            const __nv_bfloat16* __restrict__ kp, const __nv_bfloat16* __restrict__ vp,
            const __nv_bfloat16* __restrict__ shp, const __nv_bfloat16* __restrict__ hp,
            const __nv_bfloat16* __restrict__ Dp, int do_conv) {
  extern __shared__ __align__(1024) uint8_t smraw[];
  Ctx c;
  c.sb = s2u(smraw);
  c.t0 = clk32();
  asm volatile("griddepcontrol.launch_dependents;" ::: "memory");
  const int lane = threadIdx.x & 31;
  const int warp = uni(threadIdx.x >> 5);
  const int w = warp & 3, wg = warp >> 2;
  const int rank = blockIdx.x & 7, tile = blockIdx.x >> 3;
  const int ciA = 136 * tile;

  const int ciB = ciA + 72, ciH = ciA - 8;
  const int xH = (ciH >= 1024 ? 512 : 0) + rank * 64, yH = (ciH >= 1024 ? ciH - 1024 : ciH) + 1;
  const int xA = (ciA >> 10) * 512 + rank * 64, yA = ciA & 1023;
  const int xB = (ciB >> 10) * 512 + rank * 64, yB = ciB & 1023;
  const uint32_t own = xslot(c, rank);
  if (elect()) {
    const int cnt = warp < 12 ? 1 : (warp == 12 ? 8 : 12);
    if (warp == 5) {
      const uint32_t xb = barx(c, B_XOWN);
      mbar_init(xb, 1);
      fence_async_smem();
      tma2d(own, &tmX72, xA, yA, xb);
      tma2d(own + 9216, &tmX72, xB, yB, xb);
      tma2d(own + 145 * 128, &tmX7, xH, yH, xb);
    } else if (warp == 0) {
#pragma unroll
      for (int i = 0; i < 3; i++) mbar_init(barx(c, i), 1);
      fence_async_smem();
#pragma unroll
      for (int s = 0; s < 3; s++) tma2d(c.sb + OFF_RING + s * RSLOT, &tmW, (s == 0 ? 512 : (s == 1 ? 0 : 1024)) + rank * 64, rank * 64, barx(c, B_FULL + s));
    } else {
      __nanosleep(100);
    }
#pragma unroll
    for (int i = 0; i < 7; i++)
      if ((i > 0 || warp != 5) && (i > 2 || warp != 0)) mbar_init(barx(c, warp * 7 + i), cnt);
    if (warp == 0) {
      fence_async_smem();
#pragma unroll
      for (int s = 3; s < NRING; s++)
        tma2d(c.sb + OFF_RING + s * RSLOT, &tmW, (s == 3 ? 512 : (s == 4 ? 0 : 1024)) + rank * 64, (rank == 0) * 64, barx(c, B_FULL + s));
    }
    asm volatile("fence.mbarrier_init.release.cluster;" ::: "memory");
    fence_async_smem();
  }
  if (warp == 1 || warp == 2) {
    const uint32_t o = 0x3f803f80u;
    const int i = threadIdx.x - 32;
    sts128(xslot(c, i >> 3) + 144 * 128 + (i & 7) * 16, o, o, o, o);
    fence_async_smem();
  }
  __syncwarp();
  asm volatile("barrier.cluster.arrive.relaxed.aligned;" ::: "memory");
  __syncthreads();

  const int ch0 = tile * 32 + rank * 4;
  const uint32_t mtab = c.sb + OFF_STQ + (rank < 3 ? 3 * 1216 : 0);

  if (warp >= 12) {
    asm volatile("setmaxnreg.dec.sync.aligned.u32 80;");
    {
      const int b = threadIdx.x - 384;
      if (b < B_MRQ) {
        uint32_t n = 8192;
        if (b >= 32 && b < 35) n = 9216;
        if (b == B_XOWN || b >= B_XFULL) n = 151 * 128;
        if (b == B_KIN || b == B_VIN) n = KVIN;
        if (b == B_URAW) n = 16384;
        if (b == B_STQ) n = 7 * 1216;
        if (b == B_STB) n = 8 * 1152;
        mbar_expect(barx(c, b), n);
      }
    }
    cluster_wait();
    if (warp == 12) {
      const bool el = elect();
      uint32_t ph = 0, slot = 0, fb = barx(c, B_FULL + NRING);
#define ISSUE(TM, X, Y, FB)                                                        \
      {                                                                            \
        bwait(c, B_EMPTY + slot, ph);                                              \
        if (el) tma2d(c.sb + OFF_RING + slot * RSLOT, TM, X, Y, FB);               \
        fb += 8;                                                                   \
        if (++slot == NRING) { slot = 0; ph ^= 1; }                                \
      }
#pragma unroll 1
      for (int layer = 0; layer < 2; layer++) {
#pragma unroll 1
        for (int i = layer ? 0 : 2; i < 4; i++) {
          const int y = ord(rank, i) * 64;
#pragma unroll 1
          for (int part = 0; part < 3; part++) ISSUE(&tmW, ((0x201 >> (4 * part)) & 3) * 512 + rank * 64, y, fb)
        }
#pragma unroll 1
        for (int part = 0; part < 3; part++) {
          const int x = ((0x201 >> (4 * part)) & 3) * 512 + rank * 64;
#pragma unroll 1
          for (int p = ord(rank, 4); p < 8; p += (p + 1 == rank ? 2 : 1)) ISSUE(&tmW, x, p * 64, fb)
        }
        if (layer) {
#pragma unroll 1
          for (int i = 0; i < 8; i++) {
            bwait(c, B_EMPTY + slot, ph);
            if (el) tma3d(c.sb + OFF_RING + slot * RSLOT, &tmWo3, rank * 64, (i >> 1) * 16, (i & 1) * 4, fb);
            fb += 8;
            if (++slot == NRING) { slot = 0; ph ^= 1; }
          }
        } else {
#pragma unroll 1
          for (int i = 0; i < 8; i++) ISSUE(&tmWo, rank * 64, ord(rank, (OSEQ1 >> (4 * i)) & 7) * 64, fb)
          flag_wait(&g_ycnt[rank], 64u, c.t0);
#pragma unroll 1
          for (int i = 0; i < 4; i++) ISSUE(&tmY, ciA + (i >> 1) * 72, rank * 64 + (i & 1) * 32, barx(c, B_FULL + 32 + (i >> 1)))
        }
      }
      if (el && atomicAdd(&g_done, 1u) == gridDim.x - 1) {
        for (int i = 0; i < 8; i++) g_ycnt[i] = 0;
        g_ucnt = 0;
        g_done = 0;
      }
    } else if (warp == 13) {
      const int pp = ord(rank, lane & 7);
      const bool el = elect();
      const uint32_t xfb = barx(c, B_XFULL + pp);
      const uint16_t others = (uint16_t)(0xff ^ (1u << rank));
      if (lane == 0) {
        tma2d_mc(own, &tmX72, xA, yA, xfb, others);
        tma2d_mc(own + 9216, &tmX72, xB, yB, xfb, others);
        tma2d_mc(own + 145 * 128, &tmX7, xH, yH, xfb, others);
      }
#pragma unroll 1
      for (int ex = 0; ex < 3; ex++) {
        if (ex != 1) {
          bar_sync(6, 416);
          if (ex == 2) bwait(c, B_TD + 1, 1);
          if (lane >= 1 && lane < 8) {
            const uint32_t a = c.sb + OFF_STQ + rank * 1216;
            bulk_s2s(mapa(a, pp), a, 1216, mapa(barx(c, B_STQ), pp));
          }
          bwait(c, B_STQ, ex >> 1);
          if (lane == 0 && ex == 0) mbar_expect(barx(c, B_STQ), 7 * 1216);
          float2 fs[5];
#pragma unroll
          for (int i = 0; i < 5; i++) fs[i] = finish_stats(c.sb + OFF_STQ + min(lane + 32 * i, 151) * 8, 1216);
          __syncwarp();
#pragma unroll
          for (int i = 0; i < 5; i++) {
            const int r = lane + 32 * i;
            const uint32_t hi = pack2(fs[i].y, fs[i].y), lo = pack2(fs[i].y - bflo(hi), fs[i].y - bflo(hi));
            if (r < 152) {
              sts128(mtab + r * 16, hi, lo, 0, 0);
              sts32(mtab + 2432 + (r < 144 ? r + 8 : r - 144) * 4, __float_as_uint(fs[i].x));
            }
          }
          fence_async_smem();
          __syncwarp();
          if (lane == 0) mbar_arrive(barx(c, B_MRQ));
          if (ex == 0 && do_conv) {
#pragma unroll
            for (int i = 0; i < 4; i++) asm volatile("prefetch.global.L2 [%0];" ::"l"(hp + (size_t)(ch0 + i) * 2048 + lane * 64));
            if (lane == 0) asm volatile("prefetch.global.L2 [%0];" ::"l"(Dp + ch0));
          }
        }
        uint8_t* gb = (ex == 1 ? g_exX : g_exO) + (size_t)tile * 8 * XSLOT + 256;
        if (ex == 0) {
          bwait(c, B_VDONE, 0);
          if (lane >= 1 && lane < 8) mbar_expect(xfb, XSLOT - 256);
        }
        if (ex == 2 && lane < 6) mbar_expect(barx(c, B_FULL + lane), ((lane & 1) == (rank >> 2) ? 3 : 4) * 4608);
        __syncwarp();
        uint8_t* gm = gb + rank * XSLOT;
        const uint32_t xob = ex == 2 ? barx(c, B_FULL + (rank >> 2)) : barx(c, B_XFULL + rank), xos = ex == 2 ? 16 : 0;
        const uint32_t xfr = mapa(barx(c, B_XFREE), lane & 7), sp = ex ? SUBT : 4800;
        if (ex == 2) {
          bwait(c, B_X2ST, 1);
          if (lane < 8) mbar_arrive_remote(xfr);
        }
        bwait(c, ex == 1 ? B_X2ST : B_STAGED, 0);
        if (el) {
#pragma unroll
          for (int k = 0; k < 4; k++) { bulk_store(gm + k * sp, own + 256 + k * sp, ex ? 4608 : 4800); bulk_commit(); }
        }
        if (ex == 2) bwait(c, B_XFREE, 1);
        if (ex == 1) {
          const uint32_t ts = clk32();
          while (clk32() - ts < rank * STAG1) {}
          __syncwarp();
        }
        if (ex > 0) {
          bulk_wait<3>();
          const uint32_t ts = clk32(), pace = ex == 2 ? STAG : 0;
          if (el) bulk_load_mc(own + 256, gm, 4608, xob, others);
          bulk_wait<2>();
          while (clk32() - ts < pace) {}
          if (el) bulk_load_mc(own + 256 + SUBT, gm + SUBT, 4608, xob + xos, others);
          bulk_wait<1>();
          while (clk32() - ts < 2 * pace) {}
          if (el) bulk_load_mc(own + 256 + 2 * SUBT, gm + 2 * SUBT, 4608, xob + 2 * xos, others);
          bulk_wait<0>();
          __syncwarp();
          if (ex == 2 && (lane >> 1) == 3) mbar_expect(barx(c, B_FULL + lane), ((lane & 1) == (rank >> 2) ? 3 : 4) * 4608);
          while (clk32() - ts < 3 * pace) {}
          if (el) bulk_load_mc(own + 256 + 3 * SUBT, gm + 3 * SUBT, 4608, xob + 3 * xos, others);
        } else {
          bulk_wait<0>();
        }
        if (ex == 0) {
          __syncwarp();
          if (lane < 8) mbar_arrive_remote(mapa(barx(c, B_OSTORED), lane));
          bwait(c, B_OSTORED, 0);
          const int step = do_conv ? (0x30214420u >> (4 * (lane & 7))) & 7 : 0;
#pragma unroll 1
          for (int st = 0; st < (do_conv ? 5 : 1); st++) {
            if (st > 0) bwait(c, B_CVD + st - 1, 0);
            if (lane >= 1 && lane < 8 && step == st) bulk_load(xslot(c, pp) + 256, gb + pp * XSLOT, XSLOT - 256, xfb);
          }
          if (lane >= 1 && lane < 8) {
            mbar_wait(xfb, 1, c.t0);
            mbar_expect(xfb, 4 * 4608);
          }
          __syncwarp();
        }
      }
    } else {
      const int at = threadIdx.x - 448;
      const uint32_t vb = xslot(c, ord(rank, 1));
      {
        const uint8_t* pw = (const uint8_t*)wqkvp + min(blockIdx.x * 104u + at, 12287u - 64u) * 128u;
        asm volatile("prefetch.global.L2 [%0];" ::"l"(pw));
        if (at < 40) asm volatile("prefetch.global.L2 [%0];" ::"l"(pw + 64 * 128));
      }
      { const uint32_t ts = c.t0; while (clk32() - ts < PFT) __nanosleep(50); }
      if (blockIdx.x < 64) asm volatile("prefetch.global.L2 [%0];" ::"l"((const uint8_t*)wop + blockIdx.x * 8192 + at * 128));
      if (do_conv) {
#pragma unroll
        for (int i = 0; i < 2; i++) {
          const size_t o = (size_t)(rank * 256 + (tile & 1) * 128 + i * 64 + at) * 512 + (tile >> 1) * 64;
          asm volatile("prefetch.global.L2 [%0];" ::"l"(kp + o));
          asm volatile("prefetch.global.L2 [%0];" ::"l"(vp + o));
        }
        KvAddr ad;
        kv_addr(ad, lane);
        if (at == 32) {
          bwait(c, B_TD, 0);
          kv_load(own, &tmK, &tmV, shp, tile * 32, rank * 2, barx(c, B_KIN));
        }
#pragma unroll 1
        for (int it = 0; it < 4; it++) {
          const int col = 2 * (it & 1) + (warp & 1);
          if (it == 1 && at == 32) {
            bwait(c, B_TD + 1, 0);
            kv_load(vb, &tmK, &tmV, shp, tile * 32, rank * 2 + 1, barx(c, B_VIN));
          }
          __syncwarp();
          bwait(c, B_KIN + (it >> 1), 0);
          KvRegs o;
          kv_compute(o, ad, it < 2 ? own : vb, col);
          const int dst = 2 * col + (lane & 1);
          const uint32_t da = mapa(c.sb + OFF_URAW + (255 - (rank * 2 + (it >> 1)) * 16 - (lane >> 1)) * 16, dst), db = mapa(barx(c, B_URAW), dst);
#pragma unroll
          for (int ch = 0; ch < 4; ch++) {
            const uint4 v = kv_pack(o, ch);
            st_async4(da + ch * 4096, v.x, v.y, v.z, v.w, db);
          }
        }
        bar_sync(5, 64);
        if (at == 0) mbar_arrive(barx(c, B_KFREE));
#pragma unroll 1
        for (int ch = 0; ch < 4; ch += (ch ? 1 : 2)) {
          HRegs<64> hr;
          const int a2 = pin(at);
          conv_load_h(hr, hp + (size_t)(ch0 + ch) * 2048, Dp + ch0 + ch, a2);
          bwait(c, ch == 0 ? B_HFREE : (ch == 2 ? B_VDONE : B_STAGED), 0);
          conv_expand_h(hr, xslot(c, ord(rank, (HSLOT >> (4 * ch)) & 7)), a2);
          fence_async_smem();
          __syncwarp();
          if (lane == 0) mbar_arrive_n(barx(c, B_TAB + ch), 4);
        }
        if (at == 0) {
#pragma unroll 1
          for (int ch = 0; ch < 4; ch++) {
            bwait(c, B_YST + ch, 0);
            bulk_store(g_Y + (size_t)(ch0 + ch) * 2048, c.sb + OFF_URAW + ch * 4096, 4096);
            bulk_commit();
          }
          bulk_wait0();
          asm volatile("red.relaxed.gpu.global.add.u32 [%0],%1;" ::"l"(&g_ycnt[ch0 >> 6]), "r"(4u) : "memory");
        }
        __syncwarp();
      }
      if (warp == 14 && lane < 8) mbar_arrive_remote(mapa(barx(c, B_XFREE), lane));
    }
  } else {
    asm volatile("setmaxnreg.inc.sync.aligned.u32 144;");
    const int tid = w * 32 + lane;
    const int g = lane >> 2, t = lane & 3, mi = lane >> 3, r8 = lane & 7;
    const bool l0 = lane == 0;
    const uint32_t hoff = pin(w * SUBT + lane * 16);
    const uint32_t alo = (((c.sb & 0x3FFFF) + OFF_RING) >> 4) | (64u << 16);
    const uint32_t rsa = pin(own + 256 + (mi >> 1) * SUBT + (mi & 1) * 128 + r8 * 16 + warp * 256);
    uint32_t xr[10][2], yf[2][8];
    uint32_t csa0 = 0, csa1 = 0;
    const uint32_t xlo = (c.sb & 0x3FFFF) >> 4;
    const uint32_t sqd = pin(c.sb + OFF_STQ + rank * 1216 + warp * 64 + g * 8);
    uint32_t xra = pin(own + (72 * (wg & 1) + (mi >> 1) * 8 + r8) * 128 + (((2 * w + (mi & 1)) ^ r8) << 4)), xrs = 1024;
#pragma unroll 1
    for (int layer = 0; layer < 2; layer++) {
      const int sb0 = layer * 36;
      {
        float acc[76];
#pragma unroll
        for (int i = 0; i < 76; i++) acc[i] = 0.f;
        fence_regs<76>(acc);
        if (layer) bwait(c, B_STAGED, 1);
        if (layer == 0) {
      const uint32_t a1 = pin(own + (warp * 8 + r8) * 128 + ((mi ^ r8) << 4)), gs = warp < 7 ? 12 * 1024 : 0;
#pragma unroll 1
      for (int rep = 0; rep < 2; rep++) {
      uint32_t f[16];
      if (rep) bwait(c, B_XOWN, 0);
      ldsm4(f, a1); ldsm4(f + 4, a1 ^ 64); ldsm4(f + 8, a1 + gs); ldsm4(f + 12, (a1 ^ 64) + gs);
      const float2 v0 = row_stats(f, lane), v1 = row_stats(f + 8, lane);
      if ((g >> 1) == t) {
        sts64f(sqd, v0.x, v0.y);
        if (warp < 7) sts64f(sqd + 768, v1.x, v1.y);
      }
      }
    }
        bwait(c, B_FULL + sb0 + wg, 0);
        if (layer == 0) bar_sync(4, 384);
#define QKV_GEMM(WG0, WG, BLO, BHI, BSTEP, TAIL)                                                                     \
        {                                                                                                      \
          uint32_t da = alo + wg * (RSLOT >> 4), db = xlo + (BLO) + rank * (XSLOT >> 4);                       \
          uint32_t fb = barx(c, B_FULL + sb0 + 3 + wg), eb = 0, td = 0;                                        \
          int p = rank == 0, slot = 3 + wg;                                                                    \
          wg_fence();                                                                                          \
          WG0(acc, desc64(da, 0x40000040u), desc64(db, BHI), 1);                                               \
          WG(acc, desc64(da + 128, 0x40000040u), desc64(db + BSTEP, BHI), 1);                                  \
          WG(acc, desc64(da + 256, 0x40000040u), desc64(db + 2 * BSTEP, BHI), 1);                              \
          WG(acc, desc64(da + 384, 0x40000040u), desc64(db + 3 * BSTEP, BHI), 1);                              \
          wg_commit();                                                                                         \
          if (wg < 2) {                                                                 \
            _Pragma("unroll")                                                                                  \
            for (int j = 0; j < 8; j += 2) ldsm4t(&xr[j][0], xra + j * xrs);                                   \
            ldsm2t(&xr[8][0], xra + 8 * xrs);                                                                  \
          }                                                                                                    \
          fence_async_smem();                                                                                  \
          bar_arrive(6, 416);                                                                                  \
          if (layer == 0) cluster_wait();                                                                      \
          if (mbar_test(barx(c, B_XFULL + p), 0)) {                                                            \
            eb = barx(c, B_EMPTY + wg); td = barx(c, B_TD);                                                    \
          } else {                                                                                             \
            wg_wait<0>();                                                                                      \
            if (l0) { mbar_arrive_n(barx(c, B_EMPTY + wg), 3); mbar_arrive(barx(c, B_TD)); }                   \
            bwait(c, B_XFULL + p, 0);                                                                          \
          }                                                                                                    \
          mbar_wait(fb, 0, c.t0);                                                                              \
          _Pragma("unroll 1")                                                                                  \
          for (int i = 1; i < 4; i++) {                                                                        \
            da = alo + slot * (RSLOT >> 4);                                                                    \
            db = xlo + (BLO) + p * (XSLOT >> 4);                                                               \
            wg_fence();                                                                                        \
            WG(acc, desc64(da, 0x40000040u), desc64(db, BHI), 1);                                              \
            wg_commit();                                                                                       \
            wg_wait<1>();                                                                                      \
            if (l0 && eb) mbar_arrive_n(eb, 3);                                                                \
            if (l0 && td) mbar_arrive(td);                                                                     \
            WG(acc, desc64(da + 128, 0x40000040u), desc64(db + BSTEP, BHI), 1);                                \
            WG(acc, desc64(da + 256, 0x40000040u), desc64(db + 2 * BSTEP, BHI), 1);                            \
            WG(acc, desc64(da + 384, 0x40000040u), desc64(db + 3 * BSTEP, BHI), 1);                            \
            wg_commit();                                                                                       \
            eb = barx(c, B_EMPTY + slot);                                                                      \
            td = (i & 1) ? barx(c, B_TD + i) : 0;                                                              \
            slot = 2 * wg + 3 - slot;                                                                          \
            fb += i < 3 ? 24 : 24 + 24 * wg;                                                                   \
            p += p + 1 == rank ? 2 : 1;                                                                        \
            if (i < 3 && !(mbar_test(barx(c, B_XFULL + p), 0) & mbar_test(fb, 0))) {                           \
              wg_wait<0>();                                                                                    \
              if (l0) { mbar_arrive_n(eb, 3); if (td) mbar_arrive(td); }                                       \
              eb = 0; td = 0;                                                                                  \
              bwait(c, B_XFULL + p, 0);                                                                        \
              mbar_wait(fb, 0, c.t0);                                                                          \
            }                                                                                                  \
          }                                                                                                    \
          uint32_t dav[4], dbv[4], ebv[4];                                                                     \
          _Pragma("unroll")                                                                                    \
          for (int i = 0; i < 4; i++) {                                                                        \
            const int sl = (0x543210543210ull >> (4 * (((0x240 >> (4 * wg)) & 7) + i))) & 7;                   \
            dav[i] = uni(pin(alo + sl * (RSLOT >> 4)));                                                        \
            dbv[i] = uni(pin(xlo + (BLO) + ord(rank, 4 + i) * (XSLOT >> 4)));                                  \
            ebv[i] = pin(barx(c, B_EMPTY + sl));                                                               \
          }                                                                                                    \
          if (wg > 0) {                                                 \
            wg_wait<0>();                                                                                      \
            if (l0) { mbar_arrive_n(eb, 3); mbar_arrive(td); }                                                 \
            eb = 0; td = 0;                                                                                    \
            mbar_wait(fb, 0, c.t0);                                                                            \
            bar_sync(9 + wg, 256);                                                                             \
          } else {                                                                                             \
            _Pragma("unroll 1")                                                                                \
            for (int q = 7; q >= p; q--) if (q != rank) bwait(c, B_XFULL + q, 0);                              \
            mbar_wait(fb, 0, c.t0);                                                                            \
          }                                                                                                    \
          _Pragma("unroll")                                                                                    \
          for (int i = 0; i < 4; i++) {                                                                        \
            wg_fence();                                                                                        \
            WG(acc, desc64(dav[i], 0x40000040u), desc64(dbv[i], BHI), 1);                                      \
            WG(acc, desc64(dav[i] + 128, 0x40000040u), desc64(dbv[i] + BSTEP, BHI), 1);                        \
            wg_commit();                                                                                       \
            const bool ok = i == 3 || mbar_test(fb + 8 * i + 8, 0);                                            \
            wg_wait<1>();                                                                                      \
            if (i == 0) {                                                                                      \
              if (l0 && eb) { mbar_arrive_n(eb, 3); mbar_arrive(td); }                                         \
            } else if (l0) {                                                                                   \
              mbar_arrive_n(ebv[i - 1], 3);                                                                    \
              if (i == 1) mbar_arrive(barx(c, B_HFREE));                                                       \
            }                                                                                                  \
            WG(acc, desc64(dav[i] + 256, 0x40000040u), desc64(dbv[i] + 2 * BSTEP, BHI), 1);                    \
            if (i == 2 && wg < 2) bar_arrive(10 + wg, 256);                                                \
            WG(acc, desc64(dav[i] + 384, 0x40000040u), desc64(dbv[i] + 3 * BSTEP, BHI), 1);                    \
            wg_commit();                                                                                       \
            if (!ok) mbar_wait(fb + 8 * i + 8, 0, c.t0);                                                       \
          }                                                                                                    \
          eb = ebv[3];                                                                                         \
          TAIL                                                                                                 \
          wg_wait<0>();                                                                                        \
          if (l0) {                                                                                            \
            mbar_arrive_n(eb, 3);                                                                              \
          }                                                                                                    \
        }
        if (layer == 0) {
          QKV_GEMM(wg_n152, wg_n152, (1u << 16), 0x40000040u, 2, bwait(c, B_MRQ, 0);)
        } else {
          QKV_GEMM(wg_n144, wg_n144, (16u | (8u << 16)), 16u, (SUBT >> 4),
                   bwait(c, B_MRQ, 1); wg_fence(); wr_n144(acc, csa0, csa1, 0u, desc64((mtab & 0x3FFFF) >> 4, 8u)); wg_commit();)
        }
        fence_regs<76>(acc);
        xra = own + hoff + 256 + (wg & 1) * 2304; xrs = 256;
        if (layer == 0) {
          const float c0 = __shfl_sync(~0u, acc[72], lane & ~3), c1 = __shfl_sync(~0u, acc[74], lane & ~3);
          const uint32_t h = pack2(c0, c1);
          csa0 = t < 2 ? pack2(bflo(h), c0 - bflo(h)) : 0u;
          csa1 = t < 2 ? pack2(bfhi(h), c1 - bfhi(h)) : 0u;
          wg_fence();
          wr_n152(acc, csa0, csa1, 0u, desc64((mtab & 0x3FFFF) >> 4, 8u));
          wg_commit();
          wg_wait<0>();
          fence_regs<76>(acc);
        }
        if (wg == 2 && l0) mbar_arrive_n(barx(c, B_VDONE), 3);
        bwait(c, wg == 2 ? B_KQST : B_TD + 3, layer);
        const uint32_t sa = xslot(c, ord(rank, (0x632 >> (4 * wg)) & 7)) + hoff;
#pragma unroll
        for (int j = 0; j < 18; j += 2) {
          const float* a = &acc[j * 4];
          stsm4t(sa + 256 + j * 256, pack2(a[0], a[1]), pack2(a[2], a[3]), pack2(a[4], a[5]), pack2(a[6], a[7]));
        }
        stsm2t(sa, pack2(acc[72], acc[73]), pack2(acc[74], acc[75]));
        __syncwarp();
        if (wg == 2) { bar_arrive(w == 3 ? 7 : 1 + w, 64); bar_arrive(12 + w, 64); }
        else if (l0) mbar_arrive(barx(c, B_KQST));
      }
      const bool cv = layer == 0 && do_conv;
      {
        if (wg < 2) {
          const uint32_t go = hoff + wg * 2304;
          const uint32_t qb = xslot(c, ord(rank, 3)) + go + 256;
          attention(c, qb + (mi == 1 ? 128 : (mi == 2 ? -128 : 0)), qb - ((mi + 1) >> 1) * 128, xslot(c, ord(rank, 2)) + go,
                    xslot(c, ord(rank, 6)) + go, xra, mtab + 2432 + 32 + wg * 288, lane, layer,
                    wg ? tile == 7 : (layer == 1 || tile == 0), cv, (wg ? 12 : 1) + (w == 3 && !wg ? 6 : w), 1 + (w & 1));
        }
        if (cv && wg != 1) {
          const int k = wg == 0;
          HRegs<128> hr;
          conv_load_h(hr, hp + (size_t)(ch0 + 1) * 2048, Dp + ch0 + 1, tid, wg == 2);
          bwait(c, k ? B_STAGED : B_KFREE, 0);
          bwait(c, B_URAW, 0);
          URegs u0, u1;
          conv_load_u_smem(u0, c.sb + OFF_URAW + k * 8192, tid);
          conv_load_u_smem(u1, c.sb + OFF_URAW + k * 8192 + 4096, tid);
          conv_build_u(u0, xslot(c, ord(rank, 1 + k)), tid);
          conv_build_u(u1, xslot(c, ord(rank, 1 + k)) + UCH, tid);
          if (wg == 2) conv_expand_h(hr, xslot(c, ord(rank, (HSLOT >> 4) & 7)), tid);
          fence_async_smem();
          __syncwarp();
          if (lane < 2) mbar_arrive_n(barx(c, B_TAB + 2 * k + lane), (wg == 2 && lane == 1) ? 3 : 1);
        }
      }
      if (cv) {
        bwait(c, B_STAGED, 0);
#pragma unroll 1
        for (int ch = (0x102 >> (4 * wg)) & 3; ch < 4; ch += (wg == 2 ? 2 : 4)) {
          const uint32_t hs = xslot(c, ord(rank, (HSLOT >> (4 * ch)) & 7)), us = xslot(c, ord(rank, 1 + (ch >> 1))) + (ch & 1) * UCH;
          bwait(c, B_TAB + ch, 0);
          conv_channel(hs, us, c.sb + OFF_URAW + ch * 4096, 0, w, lane, barx(c, B_CVD + ch));
          fence_async_smem();
          __syncwarp();
          if (l0) mbar_arrive_n(barx(c, B_YST + ch), 3);
        }
      }
      {
        if (wg < 2) {
          float acc[36];
          const uint32_t sta = xra;
#pragma unroll
          for (int j = 0; j < 9; j++) {
            acc[j * 4 + 0] = bflo(xr[j][0]); acc[j * 4 + 1] = bfhi(xr[j][0]);
            acc[j * 4 + 2] = bflo(xr[j][1]); acc[j * 4 + 3] = bfhi(xr[j][1]);
          }
          fence_regs<36>(acc);
          const uint32_t blo = (((c.sb & 0x3FFFF) + 256 + wg * 2304) >> 4) | (8u << 16);
          const uint32_t bst = layer ? (XSLOT >> 4) : (SUBT >> 4);
          uint32_t dbv[8], xbv[8];
#pragma unroll
          for (int i = 0; i < 8; i++) {
            const int p = ord(rank, (OSEQ1 >> (4 * i)) & 7);
            dbv[i] = uni(pin(blo + (layer ? (i >> 1) * (SUBT >> 4) + (i & 1) * (XSLOT >> 2) : p * (XSLOT >> 4))));
            xbv[i] = uni(pin(layer ? barx(c, B_FULL + i) : barx(c, B_XFULL + p)));
          }
          const uint32_t fb = barx(c, B_FULL + sb0 + 24), rn = 1 + (w & 1);
          bwait(c, B_STAGED, 0);
          mbar_wait(fb, 0, c.t0);
          if (layer) bwait(c, B_FULL, 1);
          if (cv) bwait(c, B_YST + 3, 0);
#pragma unroll
          for (int i = 0; i < 8; i++) {
            const uint32_t da = alo + (i % NRING) * (RSLOT >> 4), db = dbv[i];
            wg_fence();
            wg_n72(acc, desc64(da, 0x40000040u), desc64(db, 16u), 1);
            wg_n72(acc, desc64(da + 128, 0x40000040u), desc64(db + bst, 16u), 1);
            const bool ok = i == 7 || (mbar_test(xbv[(i + 1) & 7], 1) & mbar_test(fb + 8 * i + 8, 0));
            wg_commit();
            wg_wait<1>();
            if (l0 && i > 0) mbar_arrive_n(barx(c, B_EMPTY + (i - 1) % NRING), rn);
            wg_n72(acc, desc64(da + 256, 0x40000040u), desc64(db + 2 * bst, 16u), 1);
            wg_n72(acc, desc64(da + 384, 0x40000040u), desc64(db + 3 * bst, 16u), 1);
            wg_commit();
            if (!ok) {
              mbar_wait(xbv[(i + 1) & 7], 1, c.t0);
              mbar_wait(fb + 8 * i + 8, 0, c.t0);
            }
          }
          wg_wait<0>();
          fence_regs<36>(acc);
          if (l0) mbar_arrive_n(barx(c, B_EMPTY + 1), 1 + (w & 1));
#pragma unroll
          for (int j = 0; j < 8; j += 2)
            stsm4t(sta + j * 256, pack2(acc[j * 4], acc[j * 4 + 1]), pack2(acc[j * 4 + 2], acc[j * 4 + 3]),
                   pack2(acc[j * 4 + 4], acc[j * 4 + 5]), pack2(acc[j * 4 + 6], acc[j * 4 + 7]));
          stsm2t(sta + 2048, pack2(acc[32], acc[33]), pack2(acc[34], acc[35]));
        } else if (layer == 0) {
          for (int i = 1; i < 8; i++) bwait(c, B_XFULL + ord(rank, i), 1);
        }
        const bool two = warp >= 6;
        const uint32_t sbd = sqd + (OFF_STB - OFF_STQ) - rank * (1216 - STBP);
        if (layer == 0) bwait(c, B_XFREE, 0);
        bar_sync(4, 384);
        uint32_t f[2][8];
        ldsm4(f[0], rsa); ldsm4(f[0] + 4, rsa + 2 * SUBT);
        ldsm4(f[1], rsa + 1536); ldsm4(f[1] + 4, rsa + 2 * SUBT + 1536);
        stats_send(row_stats(f[0], lane), sbd, barx(c, B_STB), lane);
        if (two) stats_send(row_stats(f[1], lane), sbd + 384, barx(c, B_STB), lane);
        if (layer == 0) {
          bwait(c, B_FULL + 32, 0);
          bwait(c, B_FULL + 33, 0);
          const uint32_t a = c.sb + OFF_RING + 2 * RSLOT + lane * 144;
          const uint32_t a0 = a + warp * 16 + (warp >= 9 ? 2 * RSLOT - 144 : 0), a1 = a + 2 * RSLOT + (two ? warp - 3 : 0) * 16;
          ldsm4t(yf[0], a0); ldsm4t(yf[0] + 4, a0 + RSLOT);
          ldsm4t(yf[1], a1); ldsm4t(yf[1] + 4, a1 + RSLOT);
          reads_done();
          __syncwarp();
          if (lane < 4) mbar_arrive(barx(c, B_EMPTY + 2 + lane));
        }
        float xu[2][16], yu[2][16];
#pragma unroll
        for (int k = 0; k < 2; k++) {
#pragma unroll
          for (int i = 0; i < 8; i++) {
            xu[k][2 * i] = bflo(f[k][i]); xu[k][2 * i + 1] = bfhi(f[k][i]);
            yu[k][2 * i] = bflo(yf[k][i]); yu[k][2 * i + 1] = bfhi(yf[k][i]);
          }
          fence_regs<16>(xu[k]);
          fence_regs<16>(yu[k]);
        }
        const uint32_t pa = c.sb + OFF_STB + t * STBP + warp * 64 + g * 8;
        bwait(c, B_STB, layer);
        if (threadIdx.x == 0) mbar_expect(barx(c, B_STB), 8 * 1152);
        {
          float s[2], q[2];
#pragma unroll
          for (int k = 0; k < 2; k++) {
            const float2 p0 = lds64f(pa + k * 384), p1 = lds64f(pa + k * 384 + 4 * STBP);
            s[k] = p0.x + p1.x; q[k] = p0.y + p1.y;
          }
#pragma unroll
          for (int o = 1; o < 4; o <<= 1)
#pragma unroll
            for (int k = 0; k < 2; k++) { s[k] += __shfl_xor_sync(~0u, s[k], o); q[k] += __shfl_xor_sync(~0u, q[k], o); }
#pragma unroll
          for (int k = 0; k < 2; k++) {
            const float mean = s[k] * (1.f / 512.f);
            float r;
            asm("rsqrt.approx.ftz.f32 %0,%1;" : "=f"(r) : "f"(fmaxf(q[k] * (1.f / 512.f) - mean * mean, 0.f) + 1e-5f));
            const float mr = -mean * r;
            if (k == 0 || two) {
#pragma unroll
              for (int i = 0; i < 8; i++)
                f[k][i] = pack2(fmaf(yu[k][2 * i], fmaf(xu[k][2 * i], r, mr), xu[k][2 * i]),
                                fmaf(yu[k][2 * i + 1], fmaf(xu[k][2 * i + 1], r, mr), xu[k][2 * i + 1]));
              stsm4(rsa + k * 1536, f[k][0], f[k][1], f[k][2], f[k][3]);
              stsm4(rsa + k * 1536 + 2 * SUBT, f[k][4], f[k][5], f[k][6], f[k][7]);
            }
          }
        }
        if (layer == 0) {
          fence_async_smem();
          __syncwarp();
          if (l0) mbar_arrive(barx(c, B_X2ST));
          const float2 v0 = row_stats(f[0], lane), v1 = row_stats(f[1], lane);
          if ((g >> 1) == t) {
            sts64f(sqd, v0.x, v0.y);
            if (two) sts64f(sqd + 384, v1.x, v1.y);
          }
          __syncwarp();
          if (l0) mbar_arrive(barx(c, B_STAGED));
        }
      }
    }
    __syncwarp();
    {
      uint4 v[4];
#pragma unroll
      for (int k = 0; k < 4; k++) v[k] = lds128(rsa + (k >> 1) * 1536 + (k & 1) * 2 * SUBT);
#pragma unroll
      for (int k = 0; k < 2; k++) {
        const int ci = ciA + (warp + k * 6) * 8 + r8;
        uint4* o = (uint4*)(outp + (size_t)(ci & 1023) * 1024 + (ci >> 10) * 512 + rank * 64 + mi * 8);
        if (k ? warp >= 6 : (warp > 0 || tile == 0)) { o[0] = v[2 * k]; o[4] = v[2 * k + 1]; }
      }
    }
  }
}


typedef CUresult (*EncFn)(CUtensorMap*, CUtensorMapDataType, cuuint32_t, void*, const cuuint64_t*, const cuuint64_t*,
                          const cuuint32_t*, const cuuint32_t*, CUtensorMapInterleave, CUtensorMapSwizzle,
                          CUtensorMapL2promotion, CUtensorMapFloatOOBfill);

static void enc2d(EncFn fn, CUtensorMap* tm, const void* base, uint64_t w, uint64_t h, uint32_t bw, uint32_t bh, bool swz) {
  cuuint64_t gd[2] = {w, h};
  cuuint64_t gs[1] = {w * 2};
  cuuint32_t bd[2] = {bw, bh};
  cuuint32_t es[2] = {1, 1};
  fn(tm, CU_TENSOR_MAP_DATA_TYPE_BFLOAT16, 2, const_cast<void*>(base), gd, gs, bd, es, CU_TENSOR_MAP_INTERLEAVE_NONE,
     swz ? CU_TENSOR_MAP_SWIZZLE_128B : CU_TENSOR_MAP_SWIZZLE_NONE, CU_TENSOR_MAP_L2_PROMOTION_L2_128B,
     CU_TENSOR_MAP_FLOAT_OOB_FILL_NONE);
}

extern "C" void kernel_launch(void* const* d_in, const int* in_sizes, int n_in, void* d_out, int out_size) {
  const __nv_bfloat16* x = (const __nv_bfloat16*)d_in[0];
  const __nv_bfloat16* wqkv = (const __nv_bfloat16*)d_in[1];
  const __nv_bfloat16* wo = (const __nv_bfloat16*)d_in[2];
  const __nv_bfloat16* kp = (const __nv_bfloat16*)d_in[4];
  const __nv_bfloat16* vp = (const __nv_bfloat16*)d_in[5];
  const __nv_bfloat16* shp = (const __nv_bfloat16*)d_in[6];
  const __nv_bfloat16* hp = (const __nv_bfloat16*)d_in[7];
  const __nv_bfloat16* Dp = (const __nv_bfloat16*)d_in[8];

  static EncFn enc = nullptr;
  static void* ybase = nullptr;
  static int fused = 0;
  cudaStream_t st = cudaStreamPerThread;
  cudaLaunchConfig_t cfg = {};
  cfg.gridDim = dim3(NT * 8);
  cfg.blockDim = dim3(512);
  cfg.dynamicSmemBytes = SMEM_MAIN;
  cfg.stream = st;
  if (!enc) {
    void* fn = nullptr;
    cudaDriverEntryPointQueryResult qr;
    cudaGetDriverEntryPoint("cuTensorMapEncodeTiled", &fn, cudaEnableDefault, &qr);
    enc = (EncFn)fn;
    cudaGetSymbolAddress(&ybase, g_Y);
    cudaFuncSetAttribute(main_kernel, cudaFuncAttributeMaxDynamicSharedMemorySize, SMEM_MAIN);
    cudaFuncSetAttribute(side_kernel, cudaFuncAttributeMaxDynamicSharedMemorySize, SMEM_SIDE);
    int ncl = 0, nsm = 0, dev = 0;
    cudaGetDevice(&dev);
    cudaDeviceGetAttribute(&nsm, cudaDevAttrMultiProcessorCount, dev);
    cudaOccupancyMaxActiveClusters(&ncl, main_kernel, &cfg);
    fused = (ncl >= NT && nsm >= NT * 8 + 8) ? 1 : 0;
    (void)cudaGetLastError();
  }
  CUtensorMap tmX72, tmX7, tmW, tmWo, tmY;
  enc2d(enc, &tmX72, x, 1024, 1024, 64, 72, true);
  enc2d(enc, &tmX7, x, 1024, 1024, 64, 7, true);
  enc2d(enc, &tmW, wqkv, 1536, 512, 64, 64, true);
  enc2d(enc, &tmWo, wo, 512, 512, 64, 64, true);
  enc2d(enc, &tmY, ybase, 2048, 512, 72, 32, false);
  __nv_bfloat16* outp = (__nv_bfloat16*)d_out;

  CUtensorMap tmWo3;
  {
    cuuint64_t gd[3] = {512, 64, 8};
    cuuint64_t gs[2] = {1024, 65536};
    cuuint32_t bd[3] = {64, 16, 4};
    cuuint32_t es[3] = {1, 1, 1};
    enc(&tmWo3, CU_TENSOR_MAP_DATA_TYPE_BFLOAT16, 3, const_cast<__nv_bfloat16*>(wo), gd, gs, bd, es, CU_TENSOR_MAP_INTERLEAVE_NONE,
        CU_TENSOR_MAP_SWIZZLE_128B, CU_TENSOR_MAP_L2_PROMOTION_L2_128B, CU_TENSOR_MAP_FLOAT_OOB_FILL_NONE);
  }
  CUtensorMap tmK, tmV;
  for (int i = 0; i < 2; i++) {
    cuuint64_t gd[3] = {512, 256, 8};
    cuuint64_t gs[2] = {8192, 1024};
    cuuint32_t bd[3] = {32, (cuuint32_t)(i ? 16 : 17), 8};
    cuuint32_t es[3] = {1, 1, 1};
    enc(i ? &tmV : &tmK, CU_TENSOR_MAP_DATA_TYPE_BFLOAT16, 3, const_cast<__nv_bfloat16*>(i ? vp : kp), gd, gs, bd, es,
        CU_TENSOR_MAP_INTERLEAVE_NONE, CU_TENSOR_MAP_SWIZZLE_64B, CU_TENSOR_MAP_L2_PROMOTION_L2_128B, CU_TENSOR_MAP_FLOAT_OOB_FILL_NONE);
  }

  if (fused) {
    cudaLaunchKernelEx(&cfg, main_kernel, tmX72, tmX7, tmW, tmWo, tmWo3, tmY, tmK, tmV, outp, wqkv, wo, kp, vp, shp, hp, Dp, 1);
    cudaLaunchConfig_t c2 = {};
    c2.gridDim = dim3(8);
    c2.blockDim = dim3(512);
    c2.dynamicSmemBytes = SMEM_SIDE;
    c2.stream = st;
    cudaLaunchAttribute a2[1];
    a2[0].id = cudaLaunchAttributeProgrammaticStreamSerialization;
    a2[0].val.programmaticStreamSerializationAllowed = 1;
    c2.attrs = a2;
    c2.numAttrs = 1;
    cudaLaunchKernelEx(&c2, side_kernel, tmK, tmV, shp, hp, Dp, 3, 120, 480, 8);
  } else {
    side_kernel<<<128, 512, SMEM_SIDE, st>>>(tmK, tmV, shp, hp, Dp, 1, 0, 0, 0);
    side_kernel<<<128, 512, SMEM_SIDE, st>>>(tmK, tmV, shp, hp, Dp, 2, 0, 0, 0);
    cudaLaunchKernelEx(&cfg, main_kernel, tmX72, tmX7, tmW, tmWo, tmWo3, tmY, tmK, tmV, outp, wqkv, wo, kp, vp, shp, hp, Dp, 0);
  }
}
```
